```python
import torch

def _softmax(x, axis=-1):
    return torch.softmax(x, dim=axis)

def _gelu(x):
    return torch.nn.functional.gelu(x, approximate='tanh')

def _silu(x):
    return torch.nn.functional.silu(x)

def _sigmoid(x):
    return torch.sigmoid(x)

def _layernorm(x, axis=-1, eps=1e-05):
    m = x.mean(dim=axis, keepdim=True)
    v = x.var(dim=axis, keepdim=True, unbiased=False)
    return (x - m) / torch.sqrt(v + eps)

def _scatter_add(tgt, idx, src, axis=0):
    return tgt.clone().index_add_(axis, idx, src)

def _segment_sum(src, seg, n):
    out = torch.zeros((n,) + src.shape[1:], dtype=src.dtype)
    return out.index_add_(0, seg, src)

def _pad(x, pw):
    flat = tuple((v for pair in reversed(pw) for v in pair))
    return torch.nn.functional.pad(x, flat)
kernel_name = 'parallel_sum__spectral_fnet__mixer_gmlp__prompt'

def setup_inputs():

    _w = lambda a: (lambda t: t.to(torch.bfloat16) if t.is_floating_point() else t)(torch.as_tensor(a))

    def _A_setup():
        B, S, D = (1, 2048, 640)
        ns = torch.arange(S)[:, None] * torch.arange(S)[None, :]
        nd = torch.arange(D)[:, None] * torch.arange(D)[None, :]
        Ws_re = torch.cos(-2.0 * torch.pi * ns / S).to(float)
        Ws_im = torch.sin(-2.0 * torch.pi * ns / S).to(float)
        Wd_re = torch.cos(-2.0 * torch.pi * nd / D).to(float)
        Wd_im = torch.sin(-2.0 * torch.pi * nd / D).to(float)
        return {'x': _w((lambda *s: torch.randn(*s, dtype=torch.bfloat16) * 0.05)(B, S, D)), 'dft_seq_re': _w(Ws_re), 'dft_seq_im': _w(Ws_im), 'dft_hid_re': _w(Wd_re), 'dft_hid_im': _w(Wd_im)}
    _A_in = _A_setup()

    def _B_setup():
        B, S, D, F = (1, 2048, 640, 1536)
        Fh = F // 2
        return {'x': _w((lambda *s: torch.randn(*s, dtype=torch.bfloat16) * 0.05)(B, S, D)), 'w_in': _w((lambda *s: torch.randn(*s, dtype=torch.bfloat16) * 0.8)(D, 2 * Fh)), 'w_sp': _w(0.01 * (lambda *s: torch.randn(*s, dtype=torch.bfloat16) * 0.8)(S, S)), 'b_sp': _w(1.0 + 0.01 * (lambda *s: torch.randn(*s, dtype=torch.bfloat16) * 0.8)(S)), 'w_out': _w((lambda *s: torch.randn(*s, dtype=torch.bfloat16) * 0.8)(Fh, D))}
    _B_in = _B_setup()
    return {'A_x': _A_in['x'], 'A_dft_seq_re': _A_in['dft_seq_re'], 'A_dft_seq_im': _A_in['dft_seq_im'], 'A_dft_hid_re': _A_in['dft_hid_re'], 'A_dft_hid_im': _A_in['dft_hid_im'], 'B_x': _B_in['x'], 'B_w_in': _B_in['w_in'], 'B_w_sp': _B_in['w_sp'], 'B_b_sp': _B_in['b_sp'], 'B_w_out': _B_in['w_out']}

def reference(A_x, A_dft_seq_re, A_dft_seq_im, A_dft_hid_re, A_dft_hid_im, B_x, B_w_in, B_w_sp, B_b_sp, B_w_out):

    def _A_ref(x, dft_seq_re, dft_seq_im, dft_hid_re, dft_hid_im):
        a = torch.einsum('bsd,ed->bse', x, dft_hid_re)
        b = torch.einsum('bsd,ed->bse', x, dft_hid_im)
        y = torch.einsum('ts,bse->bte', dft_seq_re, a) - torch.einsum('ts,bse->bte', dft_seq_im, b)
        return y

    def _B_ref(x, w_in, w_sp, b_sp, w_out):
        B, S, D = x.shape
        F = w_in.shape[-1]
        Fh = F // 2
        z = _gelu(torch.einsum('bsd,df->bsf', x, w_in))
        z1 = z[..., :Fh].clone()
        z2 = _layernorm(z[..., Fh:], axis=-1)
        g = torch.einsum('ts,bsf->btf', w_sp, z2) + b_sp[None, :, None]
        return torch.einsum('bsf,fd->bsd', z1 * g, w_out)
    x = A_x
    xn = _layernorm(x, axis=-1)
    return x + _A_ref(xn, A_dft_seq_re, A_dft_seq_im, A_dft_hid_re, A_dft_hid_im) + _B_ref(xn, B_w_in, B_w_sp, B_b_sp, B_w_out)
```

```cpp
#include <cuda.h>
#include <cuda_runtime.h>
#include <cuda_bf16.h>
#include <stdint.h>

namespace {

constexpr int SEQ = 2048, DM = 640, FH = 768;
constexpr int STAGES = 4;
constexpr int STAGE_BYTES = 40960;
constexpr int A_BYTES = 16384;
constexpr int SBUF_OFF = STAGES * STAGE_BYTES;
constexpr int SBUF_BYTES = 49152;
constexpr int BAR_OFF = SBUF_OFF + SBUF_BYTES;
constexpr int SMEM_BYTES = BAR_OFF + 1024 + 1024;
constexpr int JSPLIT = 7;
constexpr int NCTA = 128;
constexpr float LN_EPS = 1e-5f;

struct Maps {
  CUtensorMap x, hre, him, win, sre, sim, wsp, abT, z2nT, h, wout, out;
};

__device__ __align__(1024) __nv_bfloat16 g_abT[DM * 2 * SEQ];
__device__ __align__(1024) __nv_bfloat16 g_z2nT[FH * SEQ];
__device__ __align__(1024) __nv_bfloat16 g_h[SEQ * FH];
__device__ __align__(1024) float4 g_part[64 * 40 * 128];
__device__ __align__(128) float2 g_rowstat[SEQ];
__device__ __align__(128) float g_colsum[2816];
__device__ __align__(128) float2 g_z2stat[SEQ * 4];
enum { FL_PRE = 0, FL_AB = 1, FL_Z2S = 9, FL_Z2N = 25, FL_H = 29, FL_PART = 45, FL_TICKET = 109, FL_COUNT = 110 };
__device__ __align__(128) int g_flags[FL_COUNT * 8];

__device__ __forceinline__ uint32_t smem_u32(const void* p) { return (uint32_t)__cvta_generic_to_shared(p); }
__device__ __forceinline__ void mbar_init(uint32_t bar, uint32_t cnt) { asm volatile("mbarrier.init.shared::cta.b64 [%0], %1;" :: "r"(bar), "r"(cnt) : "memory"); }
__device__ __forceinline__ void mbar_expect_tx(uint32_t bar, uint32_t bytes) { asm volatile("mbarrier.arrive.expect_tx.shared::cta.b64 _, [%0], %1;" :: "r"(bar), "r"(bytes) : "memory"); }
__device__ __forceinline__ void mbar_arrive(uint32_t bar) { asm volatile("mbarrier.arrive.shared::cta.b64 _, [%0];" :: "r"(bar) : "memory"); }
__device__ __forceinline__ void mbar_arrive_cluster(uint32_t bar, uint32_t cta) {
  asm volatile("{\n.reg .b32 ra;\nmapa.shared::cluster.u32 ra, %0, %1;\nmbarrier.arrive.shared::cluster.b64 _, [ra];\n}\n" :: "r"(bar), "r"(cta) : "memory");
}
__device__ __forceinline__ void mbar_wait(uint32_t bar, uint32_t parity) {
  asm volatile("{\n.reg .pred p;\n.reg .u32 c;\nmov.u32 c, 0;\nLAB_WAIT:\n"
               "mbarrier.try_wait.parity.shared::cta.b64 p, [%0], %1;\n@p bra LAB_DONE;\n"
               "add.u32 c, c, 1;\nsetp.lt.u32 p, c, 200000;\n@p bra LAB_WAIT;\nLAB_DONE:\n}\n" :: "r"(bar), "r"(parity) : "memory");
}
__device__ __forceinline__ void tma_load(uint32_t dst, const CUtensorMap* tm, uint32_t bar, int c0, int c1) {
  asm volatile("cp.async.bulk.tensor.2d.shared::cluster.global.mbarrier::complete_tx::bytes [%0], [%1, {%3, %4}], [%2];"
    :: "r"(dst), "l"((uint64_t)tm), "r"(bar), "r"(c0), "r"(c1) : "memory");
}
__device__ __forceinline__ void tma_load_mc(uint32_t dst, const CUtensorMap* tm, uint32_t bar, int c0, int c1) {
  asm volatile("cp.async.bulk.tensor.2d.shared::cluster.global.mbarrier::complete_tx::bytes.multicast::cluster [%0], [%1, {%3, %4}], [%2], %5;"
    :: "r"(dst), "l"((uint64_t)tm), "r"(bar), "r"(c0), "r"(c1), "h"((uint16_t)3) : "memory");
}
__device__ __forceinline__ void bulk_load(uint32_t dst, const void* src, uint32_t bytes, uint32_t bar) {
  asm volatile("cp.async.bulk.shared::cluster.global.mbarrier::complete_tx::bytes [%0], [%1], %2, [%3];"
    :: "r"(dst), "l"((uint64_t)src), "r"(bytes), "r"(bar) : "memory");
}
__device__ __forceinline__ void tma_store(const CUtensorMap* tm, uint32_t src, int c0, int c1) {
  asm volatile("cp.async.bulk.tensor.2d.global.shared::cta.bulk_group [%0, {%2, %3}], [%1];"
    :: "l"((uint64_t)tm), "r"(src), "r"(c0), "r"(c1) : "memory");
}
__device__ __forceinline__ void bulk_commit() { asm volatile("cp.async.bulk.commit_group;" ::: "memory"); }
__device__ __forceinline__ void bulk_wait_read() { asm volatile("cp.async.bulk.wait_group.read 0;" ::: "memory"); }
__device__ __forceinline__ void bulk_wait_all() { asm volatile("cp.async.bulk.wait_group 0;" ::: "memory"); }
__device__ __forceinline__ void l2_prefetch(const void* p, uint32_t bytes) {
  asm volatile("cp.async.bulk.prefetch.L2.global [%0], %1;" :: "l"((uint64_t)p), "r"(bytes) : "memory");
}
__device__ __forceinline__ void prefetch_tmap(const CUtensorMap* tm) { asm volatile("prefetch.tensormap [%0];" :: "l"((uint64_t)tm) : "memory"); }
__device__ __forceinline__ void fence_async_smem() { asm volatile("fence.proxy.async.shared::cta;" ::: "memory"); }
__device__ __forceinline__ void fence_async_global() { asm volatile("fence.proxy.async.global;" ::: "memory"); }
__device__ __forceinline__ void wgmma_fence() { asm volatile("wgmma.fence.sync.aligned;" ::: "memory"); }
__device__ __forceinline__ void wgmma_commit() { asm volatile("wgmma.commit_group.sync.aligned;" ::: "memory"); }
template<int N> __device__ __forceinline__ void wgmma_wait() { asm volatile("wgmma.wait_group.sync.aligned %0;" :: "n"(N) : "memory"); }
__device__ __forceinline__ void cluster_sync() { asm volatile("barrier.cluster.arrive.aligned;\nbarrier.cluster.wait.aligned;" ::: "memory"); }
__device__ __forceinline__ void wg_sync(int wg) { asm volatile("bar.sync %0, 128;" :: "r"(wg + 1) : "memory"); }
__device__ __forceinline__ void stmatrix_x4(uint32_t addr, uint32_t r0, uint32_t r1, uint32_t r2, uint32_t r3) {
  asm volatile("stmatrix.sync.aligned.m8n8.x4.shared.b16 [%0], {%1, %2, %3, %4};" :: "r"(addr), "r"(r0), "r"(r1), "r"(r2), "r"(r3) : "memory");
}
__device__ __forceinline__ void stmatrix_x4_t(uint32_t addr, uint32_t r0, uint32_t r1, uint32_t r2, uint32_t r3) {
  asm volatile("stmatrix.sync.aligned.m8n8.x4.trans.shared.b16 [%0], {%1, %2, %3, %4};" :: "r"(addr), "r"(r0), "r"(r1), "r"(r2), "r"(r3) : "memory");
}
__device__ __forceinline__ void ldmatrix_x4(uint32_t addr, uint32_t& r0, uint32_t& r1, uint32_t& r2, uint32_t& r3) {
  asm volatile("ldmatrix.sync.aligned.m8n8.x4.shared.b16 {%0, %1, %2, %3}, [%4];" : "=r"(r0), "=r"(r1), "=r"(r2), "=r"(r3) : "r"(addr) : "memory");
}
__device__ __forceinline__ uint32_t pack_bf16(float lo, float hi) {
  uint32_t r; asm("cvt.rn.bf16x2.f32 %0, %1, %2;" : "=r"(r) : "f"(hi), "f"(lo)); return r;
}
__device__ __forceinline__ float bf_lo(uint32_t v) { return __uint_as_float(v << 16); }
__device__ __forceinline__ float bf_hi(uint32_t v) { return __uint_as_float(v & 0xffff0000u); }

__device__ __forceinline__ void flag_signal(int id) {
  asm volatile("red.release.gpu.global.add.s32 [%0], 1;" :: "l"(g_flags + id * 8) : "memory");
}
__device__ __forceinline__ void flag_wait(int id, int target) {
  const int* p = g_flags + id * 8;
  for (int it = 0; it < 4000000; it++) {
    int v;
    asm volatile("ld.acquire.gpu.global.s32 %0, [%1];" : "=r"(v) : "l"(p) : "memory");
    if (v >= target) break;
    __nanosleep(20);
  }
}

__device__ __forceinline__ float gelu(float v) {
  const float C1 = -2.3022081986f, C2 = -0.1029432397f;
  float t = v * fmaf(v * v, C2, C1);
  float e; asm("ex2.approx.ftz.f32 %0, %1;" : "=f"(e) : "f"(t));
  float r; asm("rcp.approx.ftz.f32 %0, %1;" : "=f"(r) : "f"(1.0f + e));
  return v * r;
}

template<int N, int TB> struct Wgmma;
template<int TB> struct Wgmma<160, TB> {
  static __device__ __forceinline__ void mma(float (&d)[80], uint64_t da, uint64_t db, int scale_d) {
    asm volatile("{\n.reg .pred p;\nsetp.ne.b32 p, %82, 0;\n"
      "wgmma.mma_async.sync.aligned.m64n160k16.f32.bf16.bf16 {%0, %1, %2, %3, %4, %5, %6, %7, %8, %9, %10, %11, %12, %13, %14, %15, %16, %17, %18, %19, %20, %21, %22, %23, %24, %25, %26, %27, %28, %29, %30, %31, %32, %33, %34, %35, %36, %37, %38, %39, %40, %41, %42, %43, %44, %45, %46, %47, %48, %49, %50, %51, %52, %53, %54, %55, %56, %57, %58, %59, %60, %61, %62, %63, %64, %65, %66, %67, %68, %69, %70, %71, %72, %73, %74, %75, %76, %77, %78, %79}, %80, %81, p, 1, 1, 0, %83;\n}\n"
      : "+f"(d[0]), "+f"(d[1]), "+f"(d[2]), "+f"(d[3]), "+f"(d[4]), "+f"(d[5]), "+f"(d[6]), "+f"(d[7]), "+f"(d[8]), "+f"(d[9]), "+f"(d[10]), "+f"(d[11]), "+f"(d[12]), "+f"(d[13]), "+f"(d[14]), "+f"(d[15]), "+f"(d[16]), "+f"(d[17]), "+f"(d[18]), "+f"(d[19]), "+f"(d[20]), "+f"(d[21]), "+f"(d[22]), "+f"(d[23]), "+f"(d[24]), "+f"(d[25]), "+f"(d[26]), "+f"(d[27]), "+f"(d[28]), "+f"(d[29]), "+f"(d[30]), "+f"(d[31]), "+f"(d[32]), "+f"(d[33]), "+f"(d[34]), "+f"(d[35]), "+f"(d[36]), "+f"(d[37]), "+f"(d[38]), "+f"(d[39]), "+f"(d[40]), "+f"(d[41]), "+f"(d[42]), "+f"(d[43]), "+f"(d[44]), "+f"(d[45]), "+f"(d[46]), "+f"(d[47]), "+f"(d[48]), "+f"(d[49]), "+f"(d[50]), "+f"(d[51]), "+f"(d[52]), "+f"(d[53]), "+f"(d[54]), "+f"(d[55]), "+f"(d[56]), "+f"(d[57]), "+f"(d[58]), "+f"(d[59]), "+f"(d[60]), "+f"(d[61]), "+f"(d[62]), "+f"(d[63]), "+f"(d[64]), "+f"(d[65]), "+f"(d[66]), "+f"(d[67]), "+f"(d[68]), "+f"(d[69]), "+f"(d[70]), "+f"(d[71]), "+f"(d[72]), "+f"(d[73]), "+f"(d[74]), "+f"(d[75]), "+f"(d[76]), "+f"(d[77]), "+f"(d[78]), "+f"(d[79])
      : "l"(da), "l"(db), "r"(scale_d), "n"(TB));
  }
};
template<int TB> struct Wgmma<192, TB> {
  static __device__ __forceinline__ void mma(float (&d)[96], uint64_t da, uint64_t db, int scale_d) {
    asm volatile("{\n.reg .pred p;\nsetp.ne.b32 p, %98, 0;\n"
      "wgmma.mma_async.sync.aligned.m64n192k16.f32.bf16.bf16 {%0, %1, %2, %3, %4, %5, %6, %7, %8, %9, %10, %11, %12, %13, %14, %15, %16, %17, %18, %19, %20, %21, %22, %23, %24, %25, %26, %27, %28, %29, %30, %31, %32, %33, %34, %35, %36, %37, %38, %39, %40, %41, %42, %43, %44, %45, %46, %47, %48, %49, %50, %51, %52, %53, %54, %55, %56, %57, %58, %59, %60, %61, %62, %63, %64, %65, %66, %67, %68, %69, %70, %71, %72, %73, %74, %75, %76, %77, %78, %79, %80, %81, %82, %83, %84, %85, %86, %87, %88, %89, %90, %91, %92, %93, %94, %95}, %96, %97, p, 1, 1, 0, %99;\n}\n"
      : "+f"(d[0]), "+f"(d[1]), "+f"(d[2]), "+f"(d[3]), "+f"(d[4]), "+f"(d[5]), "+f"(d[6]), "+f"(d[7]), "+f"(d[8]), "+f"(d[9]), "+f"(d[10]), "+f"(d[11]), "+f"(d[12]), "+f"(d[13]), "+f"(d[14]), "+f"(d[15]), "+f"(d[16]), "+f"(d[17]), "+f"(d[18]), "+f"(d[19]), "+f"(d[20]), "+f"(d[21]), "+f"(d[22]), "+f"(d[23]), "+f"(d[24]), "+f"(d[25]), "+f"(d[26]), "+f"(d[27]), "+f"(d[28]), "+f"(d[29]), "+f"(d[30]), "+f"(d[31]), "+f"(d[32]), "+f"(d[33]), "+f"(d[34]), "+f"(d[35]), "+f"(d[36]), "+f"(d[37]), "+f"(d[38]), "+f"(d[39]), "+f"(d[40]), "+f"(d[41]), "+f"(d[42]), "+f"(d[43]), "+f"(d[44]), "+f"(d[45]), "+f"(d[46]), "+f"(d[47]), "+f"(d[48]), "+f"(d[49]), "+f"(d[50]), "+f"(d[51]), "+f"(d[52]), "+f"(d[53]), "+f"(d[54]), "+f"(d[55]), "+f"(d[56]), "+f"(d[57]), "+f"(d[58]), "+f"(d[59]), "+f"(d[60]), "+f"(d[61]), "+f"(d[62]), "+f"(d[63]), "+f"(d[64]), "+f"(d[65]), "+f"(d[66]), "+f"(d[67]), "+f"(d[68]), "+f"(d[69]), "+f"(d[70]), "+f"(d[71]), "+f"(d[72]), "+f"(d[73]), "+f"(d[74]), "+f"(d[75]), "+f"(d[76]), "+f"(d[77]), "+f"(d[78]), "+f"(d[79]), "+f"(d[80]), "+f"(d[81]), "+f"(d[82]), "+f"(d[83]), "+f"(d[84]), "+f"(d[85]), "+f"(d[86]), "+f"(d[87]), "+f"(d[88]), "+f"(d[89]), "+f"(d[90]), "+f"(d[91]), "+f"(d[92]), "+f"(d[93]), "+f"(d[94]), "+f"(d[95])
      : "l"(da), "l"(db), "r"(scale_d), "n"(TB));
  }
};


__device__ __forceinline__ uint64_t make_desc(uint32_t addr, uint32_t lbo, uint32_t sbo) {
  return (uint64_t)((addr & 0x3FFFF) >> 4) | ((uint64_t)(lbo >> 4) << 16) | ((uint64_t)(sbo >> 4) << 32) | ((uint64_t)1 << 62);
}

struct Ctx {
  uint32_t base;
  uint32_t full0, empty0, sfree, z1rdy, turn0;
  int warp, lane;
};

__device__ __forceinline__ void release_stage(const Ctx& c, int it) {
  if (c.lane < 2) mbar_arrive_cluster(c.empty0 + 8 * (it & (STAGES - 1)), c.lane);
}

template<int N, int TB>
__device__ __forceinline__ void mainloop(const Ctx& c, float (&acc)[2][N / 2], int it0, int n, bool zero_init, bool pend, uint32_t pass_bar) {
  for (int k = 0; k < n; k++) {
    int it = it0 + k, s = it & (STAGES - 1);
    mbar_wait(c.full0 + 8 * s, (it / STAGES) & 1);
    if (pass_bar && k == n - 1 && c.lane == 0 && c.warp == 0) mbar_arrive(pass_bar);
    uint32_t sa = c.base + s * STAGE_BYTES;
    uint64_t da = make_desc(sa, 16, 1024);
    uint64_t db = TB == 0 ? make_desc(sa + A_BYTES, 16, 1024) : make_desc(sa + A_BYTES, 8192, 1024);
    wgmma_fence();
    #pragma unroll
    for (int kk = 0; kk < 4; kk++) {
      int sd = (zero_init && k == 0 && kk == 0) ? 0 : 1;
      #pragma unroll
      for (int mb = 0; mb < 2; mb++)
        Wgmma<N, TB>::mma(acc[mb], da + (uint64_t)(mb * 512 + kk * 2), db + (uint64_t)(TB == 0 ? kk * 2 : kk * 128), sd);
    }
    wgmma_commit();
    if (k > 0 || pend) { wgmma_wait<1>(); release_stage(c, it - 1); }
  }
}
template<int N>
__device__ __forceinline__ void fence_acc(float (&acc)[2][N / 2]) {
  #pragma unroll
  for (int mb = 0; mb < 2; mb++)
    #pragma unroll
    for (int e = 0; e < N / 2; e++) asm volatile("" : "+f"(acc[mb][e]) :: "memory");
}
template<int N>
__device__ __forceinline__ void drain(const Ctx& c, float (&acc)[2][N / 2], int it_last) {
  wgmma_wait<0>();
  fence_acc<N>(acc);
  release_stage(c, it_last);
}

template<int N>
__device__ __forceinline__ void apply_ln(const Ctx& c, float (&acc)[2][N / 2], int row0, const float* cs, float sgn) {
  float2 rs[2][2];
  #pragma unroll
  for (int mb = 0; mb < 2; mb++)
    #pragma unroll
    for (int hh = 0; hh < 2; hh++) {
      rs[mb][hh] = __ldcg(&g_rowstat[row0 + mb * 64 + c.warp * 16 + hh * 8 + (c.lane >> 2)]);
      rs[mb][hh].y *= sgn;
      rs[mb][hh].x *= -rs[mb][hh].y;
    }
  #pragma unroll
  for (int j = 0; j < N / 8; j++) {
    float2 s2 = __ldcg((const float2*)(cs + 8 * j + 2 * (c.lane & 3)));
    #pragma unroll
    for (int mb = 0; mb < 2; mb++) {
      acc[mb][4 * j + 0] = fmaf(acc[mb][4 * j + 0], rs[mb][0].y, rs[mb][0].x * s2.x);
      acc[mb][4 * j + 1] = fmaf(acc[mb][4 * j + 1], rs[mb][0].y, rs[mb][0].x * s2.y);
      acc[mb][4 * j + 2] = fmaf(acc[mb][4 * j + 2], rs[mb][1].y, rs[mb][1].x * s2.x);
      acc[mb][4 * j + 3] = fmaf(acc[mb][4 * j + 3], rs[mb][1].y, rs[mb][1].x * s2.y);
    }
  }
}

template<int N>
__device__ __forceinline__ void stage_transposed(const Ctx& c, float (&acc)[2][N / 2]) {
  int mi = c.lane >> 3, r = c.lane & 7;
  uint32_t a0 = c.base + SBUF_OFF + ((mi >> 1) * 8 + r) * 128 + (((2 * c.warp + (mi & 1)) ^ r) << 4);
  #pragma unroll
  for (int mb = 0; mb < 2; mb++)
    #pragma unroll
    for (int j = 0; j < N / 8; j += 2)
      stmatrix_x4_t(a0 + mb * (N * 128) + j * 1024,
                    pack_bf16(acc[mb][4 * j + 0], acc[mb][4 * j + 1]), pack_bf16(acc[mb][4 * j + 2], acc[mb][4 * j + 3]),
                    pack_bf16(acc[mb][4 * j + 4], acc[mb][4 * j + 5]), pack_bf16(acc[mb][4 * j + 6], acc[mb][4 * j + 7]));
}

__device__ __forceinline__ float quad_sum(float v) {
  v += __shfl_xor_sync(0xffffffffu, v, 1);
  v += __shfl_xor_sync(0xffffffffu, v, 2);
  return v;
}
__device__ __forceinline__ float sum8(uint4 v) {
  return ((bf_lo(v.x) + bf_hi(v.x)) + (bf_lo(v.y) + bf_hi(v.y))) + ((bf_lo(v.z) + bf_hi(v.z)) + (bf_lo(v.w) + bf_hi(v.w)));
}
__device__ __forceinline__ float sq8(uint4 v, float m) {
  float a0 = bf_lo(v.x) - m, a1 = bf_hi(v.x) - m, a2 = bf_lo(v.y) - m, a3 = bf_hi(v.y) - m;
  float a4 = bf_lo(v.z) - m, a5 = bf_hi(v.z) - m, a6 = bf_lo(v.w) - m, a7 = bf_hi(v.w) - m;
  return ((a0 * a0 + a1 * a1) + (a2 * a2 + a3 * a3)) + ((a4 * a4 + a5 * a5) + (a6 * a6 + a7 * a7));
}

__device__ __forceinline__ void prepass(const Ctx& c, int tid, const __nv_bfloat16* x, const __nv_bfloat16* hre,
                                        const __nv_bfloat16* him, const __nv_bfloat16* win, float* red) {
  int cta = blockIdx.x;
  int sub = tid & 7, grp = tid >> 3;
  uint4 vx[10], vh[10], vw[10];
  const uint4* px = (const uint4*)(x + (size_t)(cta * 16 + grp) * DM) + sub;
  #pragma unroll
  for (int i = 0; i < 10; i++) vx[i] = __ldg(px + 8 * i);
  int hr = cta * 10 + grp;
  bool do_h = grp < 10;
  const uint4* ph = (const uint4*)((hr < DM ? hre : him) + (size_t)(hr < DM ? hr : hr - DM) * DM) + sub;
  #pragma unroll
  for (int i = 0; i < 10; i++) vh[i] = do_h ? __ldg(ph + 8 * i) : make_uint4(0, 0, 0, 0);
  bool do_w = cta < 96;
  const uint4* pw = (const uint4*)(win + (size_t)(tid >> 1) * (2 * FH) + cta * 16) + (tid & 1);
  #pragma unroll
  for (int i = 0; i < 10; i++) vw[i] = do_w ? __ldg(pw + (size_t)i * 64 * (2 * FH / 8)) : make_uint4(0, 0, 0, 0);
  float s = 0.f;
  #pragma unroll
  for (int i = 0; i < 10; i++) s += sum8(vx[i]);
  s += __shfl_xor_sync(0xffffffffu, s, 1); s += __shfl_xor_sync(0xffffffffu, s, 2); s += __shfl_xor_sync(0xffffffffu, s, 4);
  float mean = s * (1.0f / DM), q = 0.f;
  #pragma unroll
  for (int i = 0; i < 10; i++) q += sq8(vx[i], mean);
  q += __shfl_xor_sync(0xffffffffu, q, 1); q += __shfl_xor_sync(0xffffffffu, q, 2); q += __shfl_xor_sync(0xffffffffu, q, 4);
  if (sub == 0) g_rowstat[cta * 16 + grp] = make_float2(mean, rsqrtf(q * (1.0f / DM) + LN_EPS));
  float hs = 0.f;
  #pragma unroll
  for (int i = 0; i < 10; i++) hs += sum8(vh[i]);
  hs += __shfl_xor_sync(0xffffffffu, hs, 1); hs += __shfl_xor_sync(0xffffffffu, hs, 2); hs += __shfl_xor_sync(0xffffffffu, hs, 4);
  if (sub == 0 && do_h) g_colsum[hr] = hs;
  float w[8];
  #pragma unroll
  for (int e = 0; e < 8; e++) w[e] = 0.f;
  #pragma unroll
  for (int i = 0; i < 10; i++) {
    w[0] += bf_lo(vw[i].x); w[1] += bf_hi(vw[i].x); w[2] += bf_lo(vw[i].y); w[3] += bf_hi(vw[i].y);
    w[4] += bf_lo(vw[i].z); w[5] += bf_hi(vw[i].z); w[6] += bf_lo(vw[i].w); w[7] += bf_hi(vw[i].w);
  }
  #pragma unroll
  for (int e = 0; e < 8; e++) {
    #pragma unroll
    for (int o = 2; o < 32; o <<= 1) w[e] += __shfl_xor_sync(0xffffffffu, w[e], o);
  }
  if (c.lane < 2) {
    #pragma unroll
    for (int e = 0; e < 8; e++) red[c.warp * 16 + c.lane * 8 + e] = w[e];
  }
  wg_sync(1);
  if (tid < 16 && do_w) g_colsum[1280 + cta * 16 + tid] = (red[tid] + red[16 + tid]) + (red[32 + tid] + red[48 + tid]);
  __threadfence();
  wg_sync(1);
  if (tid == 0) flag_signal(FL_PRE);
}

__device__ __forceinline__ void wg_flag_wait(int wg, int tid, int id, int target) {
  if (tid == 0) flag_wait(id, target);
  wg_sync(wg);
}

__device__ __forceinline__ void take_ticket() {
  int t = atomicAdd(&g_flags[FL_TICKET * 8], 1);
  if (t == NCTA - 1) {
    for (int i = 0; i < FL_COUNT; i++) g_flags[i * 8] = 0;
  }
}

__global__ void __cluster_dims__(2, 1, 1) __launch_bounds__(384, 1)
fused_kernel(const __grid_constant__ Maps maps, const __nv_bfloat16* __restrict__ x, const __nv_bfloat16* __restrict__ hre,
             const __nv_bfloat16* __restrict__ him, const __nv_bfloat16* __restrict__ win, const __nv_bfloat16* __restrict__ sre,
             const __nv_bfloat16* __restrict__ sim, const __nv_bfloat16* __restrict__ wsp, const __nv_bfloat16* __restrict__ bsp,
             const __nv_bfloat16* __restrict__ wout) {
  extern __shared__ uint8_t smem_raw[];
  Ctx c;
  c.base = (smem_u32(smem_raw) + 1023) & ~1023u;
  c.full0 = c.base + BAR_OFF; c.empty0 = c.full0 + 8 * STAGES; c.sfree = c.empty0 + 8 * STAGES; c.z1rdy = c.sfree + 8; c.turn0 = c.z1rdy + 8;
  const int wg = __shfl_sync(0xffffffffu, threadIdx.x >> 7, 0), tid = threadIdx.x & 127;
  c.warp = __shfl_sync(0xffffffffu, tid >> 5, 0); c.lane = tid & 31;
  const int rank = blockIdx.x & 1, pair = blockIdx.x >> 1;
  const bool isG = pair & 1;
  const int q = pair >> 1, rb = q >> 1, ct = (q & 1) * 2 + rank;
  const int row0 = rb * 128;

  if (threadIdx.x == 0) {
    for (int s = 0; s < STAGES; s++) { mbar_init(c.full0 + 8 * s, 1); mbar_init(c.empty0 + 8 * s, 8); }
    mbar_init(c.sfree, 1); mbar_init(c.z1rdy, 128); mbar_init(c.turn0, 1); mbar_init(c.turn0 + 8, 1);
    asm volatile("fence.mbarrier_init.release.cluster;" ::: "memory");
  }
  __syncthreads();
  cluster_sync();

  if (wg == 2) {
    asm volatile("setmaxnreg.dec.sync.aligned.u32 40;");
    if (tid == 0) {
      int it = 0;
      uint32_t sa = 0, fb = 0;
      auto acquire = [&](uint32_t bytes) {
        int s = it & (STAGES - 1);
        mbar_wait(c.empty0 + 8 * s, ((it / STAGES) & 1) ^ 1);
        sa = c.base + s * STAGE_BYTES; fb = c.full0 + 8 * s;
        mbar_expect_tx(fb, bytes);
        it++;
      };
      auto loadA = [&](const CUtensorMap* tm, int kc) { tma_load_mc(sa + rank * 8192, tm, fb, kc, row0 + rank * 64); };
      if (!isG) {
        for (int t = 0; t < 2; t++)
          for (int k = 0; k < 10; k++) {
            acquire(A_BYTES + 160 * 128);
            loadA(&maps.x, k * 64);
            tma_load(sa + A_BYTES, t == 0 ? &maps.hre : &maps.him, fb, k * 64, ct * 160);
          }
        for (int kk = 0; kk < 64 - JSPLIT; kk++) {
          acquire(A_BYTES + 160 * 128);
          loadA(kk < 32 ? &maps.sre : &maps.sim, (kk & 31) * 64);
          if ((kk & 31) == 0) { flag_wait(FL_AB + (kk >> 5) * 4 + ct, 16); fence_async_global(); }
          tma_load(sa + A_BYTES, &maps.abT, fb, kk * 64, ct * 160);
        }
        take_ticket();
      } else {
        for (int t = 0; t < 2; t++)
          for (int k = 0; k < 10; k++) {
            acquire(A_BYTES + 192 * 128);
            loadA(&maps.x, k * 64);
            int n0 = (t == 0 ? FH : 0) + ct * 192;
            for (int b = 0; b < 3; b++) tma_load(sa + A_BYTES + b * 8192, &maps.win, fb, n0 + b * 64, k * 64);
          }
        for (int k = 0; k < 32; k++) {
          acquire(A_BYTES + 192 * 128);
          loadA(&maps.wsp, k * 64);
          if (k == 0) { flag_wait(FL_Z2N + ct, 16); fence_async_global(); }
          tma_load(sa + A_BYTES, &maps.z2nT, fb, k * 64, ct * 192);
        }
        flag_wait(FL_AB + 4 + ct, 16); fence_async_global();
        for (int kk = 64 - JSPLIT; kk < 64; kk++) {
          acquire(A_BYTES + 160 * 128);
          loadA(&maps.sim, (kk & 31) * 64);
          tma_load(sa + A_BYTES, &maps.abT, fb, kk * 64, ct * 160);
        }
        for (int k = 0; k < 12; k++) {
          acquire(A_BYTES + 192 * 128);
          for (int b = 0; b < 3; b++) tma_load(sa + A_BYTES + b * 8192, &maps.wout, fb, ct * 160 + b * 64, k * 64);
          if (k == 0) { flag_wait(FL_H + rb, 4); fence_async_global(); }
          loadA(&maps.h, k * 64);
        }
        for (int p = 0; p < 2; p++) {
          acquire(STAGE_BYTES);
          if (p == 0) { flag_wait(FL_PART + rb * 4 + ct, 1); fence_async_global(); }
          bulk_load(sa, g_part + ((size_t)(rb * 4 + ct) * 40 + p * 20) * 128, STAGE_BYTES, fb);
        }
        take_ticket();
      }
    } else if (c.warp == 1) {
      __nanosleep(1500);
      int r = row0 + ct * 32 + c.lane;
      if (!isG) {
        for (int sgm = 0; sgm < 4; sgm++) l2_prefetch(sre + (size_t)r * SEQ + sgm * 512, 1024);
        __nanosleep(3000);
        for (int sgm = 0; sgm < 4; sgm++) l2_prefetch(sim + (size_t)r * SEQ + sgm * 512, 1024);
      } else {
        for (int sgm = 0; sgm < 4; sgm++) l2_prefetch(wsp + (size_t)r * SEQ + sgm * 512, 1024);
        if (c.lane < 12) l2_prefetch(wout + (size_t)((rb * 4 + ct) * 12 + c.lane) * DM, DM * 2);
      }
    }
  } else {
    asm volatile("setmaxnreg.inc.sync.aligned.u32 232;");
    const uint32_t sbuf = c.base + SBUF_OFF;
    if (wg == 1) prepass(c, tid, x, hre, him, win, (float*)(smem_raw + (c.base - smem_u32(smem_raw)) + BAR_OFF + 256));
    if (!isG) {
      {
        float acc[2][80];
        if (wg == 1) mbar_wait(c.turn0 + 8, 0);
        mainloop<160, 0>(c, acc, wg * 10, 10, true, false, c.turn0 + 8 * (wg ^ 1));
        drain<160>(c, acc, wg * 10 + 9);
        wg_flag_wait(wg, tid, FL_PRE, NCTA);
        apply_ln<160>(c, acc, row0, g_colsum + wg * DM + ct * 160, wg == 0 ? 1.0f : -1.0f);
        if (wg == 1) mbar_wait(c.sfree, 0);
        stage_transposed<160>(c, acc);
        fence_async_smem();
        wg_sync(wg);
        if (tid == 0) {
          tma_store(&maps.abT, sbuf, wg * SEQ + row0, ct * 160);
          tma_store(&maps.abT, sbuf + 160 * 128, wg * SEQ + row0 + 64, ct * 160);
          bulk_commit();
          bulk_wait_all();
          if (wg == 0) mbar_arrive(c.sfree);
          fence_async_global();
          flag_signal(FL_AB + wg * 4 + ct);
        }
      }
      if (wg == 0) {
        float acc[2][80];
        #pragma unroll
        for (int mb = 0; mb < 2; mb++)
          #pragma unroll
          for (int hh = 0; hh < 2; hh++) {
            const uint32_t* px = (const uint32_t*)(x + (size_t)(row0 + mb * 64 + c.warp * 16 + hh * 8 + (c.lane >> 2)) * DM + ct * 160) + (c.lane & 3);
            #pragma unroll
            for (int j = 0; j < 20; j++) {
              uint32_t v = __ldg(px + 4 * j);
              acc[mb][4 * j + 2 * hh] = bf_lo(v); acc[mb][4 * j + 2 * hh + 1] = bf_hi(v);
            }
          }
        fence_acc<160>(acc);
        mbar_wait(c.turn0, 0);
        mainloop<160, 0>(c, acc, 20, 64 - JSPLIT, false, false, 0);
        drain<160>(c, acc, 20 + 64 - JSPLIT - 1);
        float4* pp = g_part + (size_t)(rb * 4 + ct) * 40 * 128 + tid;
        #pragma unroll
        for (int mb = 0; mb < 2; mb++)
          #pragma unroll
          for (int j = 0; j < 20; j++)
            __stcg(pp + (mb * 20 + j) * 128, make_float4(acc[mb][4 * j], acc[mb][4 * j + 1], acc[mb][4 * j + 2], acc[mb][4 * j + 3]));
        __threadfence();
        wg_sync(0);
        if (tid == 0) flag_signal(FL_PART + rb * 4 + ct);
      }
    } else if (wg == 0) {
      {
        float acc[2][96];
        mainloop<192, 1>(c, acc, 0, 10, true, false, c.turn0 + 8);
        drain<192>(c, acc, 9);
        wg_flag_wait(0, tid, FL_PRE, NCTA);
        apply_ln<192>(c, acc, row0, g_colsum + 1280 + FH + ct * 192, 1.0f);
        float sm[2][2];
        #pragma unroll
        for (int mb = 0; mb < 2; mb++) {
          float s0 = 0.f, s1 = 0.f;
          #pragma unroll
          for (int j = 0; j < 24; j++) {
            #pragma unroll
            for (int e = 0; e < 4; e++) acc[mb][4 * j + e] = gelu(acc[mb][4 * j + e]);
            s0 += acc[mb][4 * j] + acc[mb][4 * j + 1];
            s1 += acc[mb][4 * j + 2] + acc[mb][4 * j + 3];
          }
          sm[mb][0] = quad_sum(s0) * (1.0f / 192); sm[mb][1] = quad_sum(s1) * (1.0f / 192);
        }
        #pragma unroll
        for (int mb = 0; mb < 2; mb++) {
          float q0 = 0.f, q1 = 0.f;
          #pragma unroll
          for (int j = 0; j < 24; j++) {
            float d0 = acc[mb][4 * j] - sm[mb][0], d1 = acc[mb][4 * j + 1] - sm[mb][0];
            float d2 = acc[mb][4 * j + 2] - sm[mb][1], d3 = acc[mb][4 * j + 3] - sm[mb][1];
            q0 = fmaf(d0, d0, q0); q0 = fmaf(d1, d1, q0); q1 = fmaf(d2, d2, q1); q1 = fmaf(d3, d3, q1);
          }
          q0 = quad_sum(q0); q1 = quad_sum(q1);
          if ((c.lane & 3) == 0) {
            int r = row0 + mb * 64 + c.warp * 16 + (c.lane >> 2);
            __stcg(&g_z2stat[r * 4 + ct], make_float2(sm[mb][0], q0));
            __stcg(&g_z2stat[(r + 8) * 4 + ct], make_float2(sm[mb][1], q1));
          }
        }
        __threadfence();
        wg_sync(0);
        if (tid == 0) { flag_signal(FL_Z2S + rb); flag_wait(FL_Z2S + rb, 4); }
        wg_sync(0);
        #pragma unroll
        for (int mb = 0; mb < 2; mb++)
          #pragma unroll
          for (int hh = 0; hh < 2; hh++) {
            int r = row0 + mb * 64 + c.warp * 16 + hh * 8 + (c.lane >> 2);
            float4 p0 = __ldcg((const float4*)&g_z2stat[r * 4]), p1 = __ldcg((const float4*)&g_z2stat[r * 4 + 2]);
            float mean = 0.25f * ((p0.x + p0.z) + (p1.x + p1.z));
            float d0 = p0.x - mean, d1 = p0.z - mean, d2 = p1.x - mean, d3 = p1.z - mean;
            float m2 = ((p0.y + p0.w) + (p1.y + p1.w)) + 192.0f * ((d0 * d0 + d1 * d1) + (d2 * d2 + d3 * d3));
            float rstd = rsqrtf(m2 * (1.0f / FH) + LN_EPS), off = -mean * rstd;
            #pragma unroll
            for (int j = 0; j < 24; j++) {
              acc[mb][4 * j + 2 * hh] = fmaf(acc[mb][4 * j + 2 * hh], rstd, off);
              acc[mb][4 * j + 2 * hh + 1] = fmaf(acc[mb][4 * j + 2 * hh + 1], rstd, off);
            }
          }
        stage_transposed<192>(c, acc);
        fence_async_smem();
        wg_sync(0);
        if (tid == 0) {
          tma_store(&maps.z2nT, sbuf, row0, ct * 192);
          tma_store(&maps.z2nT, sbuf + 192 * 128, row0 + 64, ct * 192);
          bulk_commit();
          bulk_wait_all();
          mbar_arrive(c.sfree);
          fence_async_global();
          flag_signal(FL_Z2N + ct);
        }
      }
      {
        float acc[2][96];
        #pragma unroll
        for (int mb = 0; mb < 2; mb++)
          #pragma unroll
          for (int hh = 0; hh < 2; hh++) {
            float b = __bfloat162float(bsp[row0 + mb * 64 + c.warp * 16 + hh * 8 + (c.lane >> 2)]);
            #pragma unroll
            for (int j = 0; j < 24; j++) { acc[mb][4 * j + 2 * hh] = b; acc[mb][4 * j + 2 * hh + 1] = b; }
          }
        fence_acc<192>(acc);
        mbar_wait(c.turn0, 0);
        mainloop<192, 0>(c, acc, 20, 32, false, false, c.turn0 + 8);
        drain<192>(c, acc, 51);
        mbar_wait(c.z1rdy, 0);
        int mi = c.lane >> 3, r = c.lane & 7;
        #pragma unroll
        for (int mb = 0; mb < 2; mb++)
          #pragma unroll
          for (int j = 0; j < 24; j += 2) {
            uint32_t ad = sbuf + (j >> 3) * 16384 + (mb * 64 + c.warp * 16 + (mi & 1) * 8 + r) * 128 + ((((j & 7) + (mi >> 1)) ^ r) << 4);
            uint32_t z0, z1, z2, z3;
            ldmatrix_x4(ad, z0, z1, z2, z3);
            stmatrix_x4(ad, pack_bf16(acc[mb][4 * j + 0] * bf_lo(z0), acc[mb][4 * j + 1] * bf_hi(z0)),
                            pack_bf16(acc[mb][4 * j + 2] * bf_lo(z1), acc[mb][4 * j + 3] * bf_hi(z1)),
                            pack_bf16(acc[mb][4 * j + 4] * bf_lo(z2), acc[mb][4 * j + 5] * bf_hi(z2)),
                            pack_bf16(acc[mb][4 * j + 6] * bf_lo(z3), acc[mb][4 * j + 7] * bf_hi(z3)));
          }
        fence_async_smem();
        wg_sync(0);
        if (tid == 0) {
          for (int b = 0; b < 3; b++)
            for (int hf = 0; hf < 2; hf++)
              tma_store(&maps.h, sbuf + b * 16384 + hf * 8192, ct * 192 + b * 64, row0 + hf * 64);
          bulk_commit();
          bulk_wait_all();
          mbar_arrive(c.sfree);
          fence_async_global();
          flag_signal(FL_H + rb);
        }
      }
    } else {
      {
        float acc[2][96];
        mbar_wait(c.turn0 + 8, 0);
        mainloop<192, 1>(c, acc, 10, 10, true, false, c.turn0);
        drain<192>(c, acc, 19);
        wg_flag_wait(1, tid, FL_PRE, NCTA);
        apply_ln<192>(c, acc, row0, g_colsum + 1280 + ct * 192, 1.0f);
        mbar_wait(c.sfree, 0);
        int mi = c.lane >> 3, r = c.lane & 7;
        #pragma unroll
        for (int mb = 0; mb < 2; mb++)
          #pragma unroll
          for (int j = 0; j < 24; j += 2) {
            uint32_t ad = sbuf + (j >> 3) * 16384 + (mb * 64 + c.warp * 16 + (mi & 1) * 8 + r) * 128 + ((((j & 7) + (mi >> 1)) ^ r) << 4);
            stmatrix_x4(ad, pack_bf16(gelu(acc[mb][4 * j + 0]), gelu(acc[mb][4 * j + 1])),
                            pack_bf16(gelu(acc[mb][4 * j + 2]), gelu(acc[mb][4 * j + 3])),
                            pack_bf16(gelu(acc[mb][4 * j + 4]), gelu(acc[mb][4 * j + 5])),
                            pack_bf16(gelu(acc[mb][4 * j + 6]), gelu(acc[mb][4 * j + 7])));
          }
        mbar_arrive(c.z1rdy);
      }
      {
        float acc[2][80];
        mbar_wait(c.turn0 + 8, 1);
        mainloop<160, 0>(c, acc, 52, JSPLIT, true, false, 0);
        mainloop<160, 1>(c, acc, 52 + JSPLIT, 12, false, true, 0);
        drain<160>(c, acc, 52 + JSPLIT + 11);
        mbar_wait(c.sfree, 1);
        int mi = c.lane >> 3, r = c.lane & 7;
        #pragma unroll
        for (int mb = 0; mb < 2; mb++) {
          const int it = 52 + JSPLIT + 12 + mb, s = it & (STAGES - 1);
          mbar_wait(c.full0 + 8 * s, (it / STAGES) & 1);
          const float4* pp = (const float4*)(smem_raw + (c.base - smem_u32(smem_raw)) + s * STAGE_BYTES) + tid;
          int row = mb * 64 + c.warp * 16 + (mi & 1) * 8 + r;
          #pragma unroll
          for (int j = 0; j < 20; j += 2) {
            float4 p0 = pp[j * 128], p1 = pp[(j + 1) * 128];
            uint32_t ad = sbuf + (j >> 2) * 8192 + row * 64 + ((((j & 3) + (mi >> 1)) ^ ((row >> 1) & 3)) << 4);
            stmatrix_x4(ad, pack_bf16(acc[mb][4 * j + 0] + p0.x, acc[mb][4 * j + 1] + p0.y),
                            pack_bf16(acc[mb][4 * j + 2] + p0.z, acc[mb][4 * j + 3] + p0.w),
                            pack_bf16(acc[mb][4 * j + 4] + p1.x, acc[mb][4 * j + 5] + p1.y),
                            pack_bf16(acc[mb][4 * j + 6] + p1.z, acc[mb][4 * j + 7] + p1.w));
          }
        }
        fence_async_smem();
        wg_sync(1);
        if (tid == 0) {
          for (int b = 0; b < 5; b++) tma_store(&maps.out, sbuf + b * 8192, ct * 160 + b * 32, row0);
          bulk_commit();
          bulk_wait_read();
        }
      }
    }
  }
  cluster_sync();
}

typedef CUresult (*EncodeFn)(CUtensorMap*, CUtensorMapDataType, cuuint32_t, void*, const cuuint64_t*, const cuuint64_t*,
                             const cuuint32_t*, const cuuint32_t*, CUtensorMapInterleave, CUtensorMapSwizzle,
                             CUtensorMapL2promotion, CUtensorMapFloatOOBfill);

void make_map(EncodeFn enc, CUtensorMap* m, const void* p, int rows, int cols, int box_rows, int box_cols, CUtensorMapSwizzle sw) {
  cuuint64_t gd[2] = {(cuuint64_t)cols, (cuuint64_t)rows};
  cuuint64_t gs[1] = {(cuuint64_t)cols * 2};
  cuuint32_t bd[2] = {(cuuint32_t)box_cols, (cuuint32_t)box_rows};
  cuuint32_t es[2] = {1, 1};
  enc(m, CU_TENSOR_MAP_DATA_TYPE_BFLOAT16, 2, (void*)p, gd, gs, bd, es, CU_TENSOR_MAP_INTERLEAVE_NONE, sw,
      CU_TENSOR_MAP_L2_PROMOTION_L2_256B, CU_TENSOR_MAP_FLOAT_OOB_FILL_NONE);
}

}

extern "C" void kernel_launch(void* const* d_in, const int* in_sizes, int n_in, void* d_out, int out_size) {
  const __nv_bfloat16* x = (const __nv_bfloat16*)d_in[0];
  const __nv_bfloat16* sre = (const __nv_bfloat16*)d_in[1];
  const __nv_bfloat16* sim = (const __nv_bfloat16*)d_in[2];
  const __nv_bfloat16* hre = (const __nv_bfloat16*)d_in[3];
  const __nv_bfloat16* him = (const __nv_bfloat16*)d_in[4];
  const __nv_bfloat16* win = (const __nv_bfloat16*)d_in[6];
  const __nv_bfloat16* wsp = (const __nv_bfloat16*)d_in[7];
  const __nv_bfloat16* bsp = (const __nv_bfloat16*)d_in[8];
  const __nv_bfloat16* wout = (const __nv_bfloat16*)d_in[9];

  void* fn = nullptr;
  cudaDriverEntryPointQueryResult qr;
  cudaGetDriverEntryPoint("cuTensorMapEncodeTiled", &fn, cudaEnableDefault, &qr);
  EncodeFn enc = (EncodeFn)fn;
  void *p_abT, *p_z2nT, *p_h;
  cudaGetSymbolAddress(&p_abT, g_abT);
  cudaGetSymbolAddress(&p_z2nT, g_z2nT);
  cudaGetSymbolAddress(&p_h, g_h);
  Maps m;
  const CUtensorMapSwizzle S128 = CU_TENSOR_MAP_SWIZZLE_128B;
  make_map(enc, &m.x, x, SEQ, DM, 64, 64, S128);
  make_map(enc, &m.hre, hre, DM, DM, 160, 64, S128);
  make_map(enc, &m.him, him, DM, DM, 160, 64, S128);
  make_map(enc, &m.win, win, DM, 2 * FH, 64, 64, S128);
  make_map(enc, &m.sre, sre, SEQ, SEQ, 64, 64, S128);
  make_map(enc, &m.sim, sim, SEQ, SEQ, 64, 64, S128);
  make_map(enc, &m.wsp, wsp, SEQ, SEQ, 64, 64, S128);
  make_map(enc, &m.abT, p_abT, DM, 2 * SEQ, 160, 64, S128);
  make_map(enc, &m.z2nT, p_z2nT, FH, SEQ, 192, 64, S128);
  make_map(enc, &m.h, p_h, SEQ, FH, 64, 64, S128);
  make_map(enc, &m.wout, wout, FH, DM, 64, 64, S128);
  make_map(enc, &m.out, d_out, SEQ, DM, 128, 32, CU_TENSOR_MAP_SWIZZLE_64B);
  cudaFuncSetAttribute(fused_kernel, cudaFuncAttributeMaxDynamicSharedMemorySize, SMEM_BYTES);
  fused_kernel<<<NCTA, 384, SMEM_BYTES>>>(m, x, hre, him, win, sre, sim, wsp, bsp, wout);
}
```

```cpp
#include <cuda.h>
#include <cuda_runtime.h>
#include <cuda_bf16.h>
#include <stdint.h>

namespace {

constexpr int SEQ = 2048, DM = 640, FH = 768;
constexpr int STAGES = 4;
constexpr int STAGE_BYTES = 40960;
constexpr int A_BYTES = 16384;
constexpr int SBUF_OFF = STAGES * STAGE_BYTES;
constexpr int SBUF_BYTES = 49152;
constexpr int BAR_OFF = SBUF_OFF + SBUF_BYTES;
constexpr int SMEM_BYTES = BAR_OFF + 1024 + 1024;
constexpr int JSPLIT = 7;
constexpr int NCTA = 128;
constexpr float LN_EPS = 1e-5f;

struct Maps {
  CUtensorMap x, hre, him, win, sre, sim, wsp, abT, z2nT, h, wout, out;
};

__device__ __align__(1024) __nv_bfloat16 g_abT[DM * 2 * SEQ];
__device__ __align__(1024) __nv_bfloat16 g_z2nT[FH * SEQ];
__device__ __align__(1024) __nv_bfloat16 g_h[SEQ * FH];
__device__ __align__(1024) float4 g_part[64 * 40 * 128];
__device__ __align__(128) float2 g_rowstat[SEQ];
__device__ __align__(128) float g_colsum[2816];
__device__ __align__(128) float2 g_z2stat[SEQ * 4];
enum { FL_PRE = 0, FL_AB = 1, FL_Z2S = 9, FL_Z2N = 25, FL_H = 29, FL_PART = 45, FL_TICKET = 109, FL_COUNT = 110 };
__device__ __align__(128) int g_flags[FL_COUNT * 8];

#define TSTAMP(id)
#define TSTAMP_G(id)
__device__ __forceinline__ uint32_t smem_u32(const void* p) { return (uint32_t)__cvta_generic_to_shared(p); }
__device__ __forceinline__ void mbar_init(uint32_t bar, uint32_t cnt) { asm volatile("mbarrier.init.shared::cta.b64 [%0], %1;" :: "r"(bar), "r"(cnt) : "memory"); }
__device__ __forceinline__ void mbar_expect_tx(uint32_t bar, uint32_t bytes) { asm volatile("mbarrier.arrive.expect_tx.shared::cta.b64 _, [%0], %1;" :: "r"(bar), "r"(bytes) : "memory"); }
__device__ __forceinline__ void mbar_arrive(uint32_t bar) { asm volatile("mbarrier.arrive.shared::cta.b64 _, [%0];" :: "r"(bar) : "memory"); }
__device__ __forceinline__ void mbar_arrive_cluster(uint32_t bar, uint32_t cta) {
  asm volatile("{\n.reg .b32 ra;\nmapa.shared::cluster.u32 ra, %0, %1;\nmbarrier.arrive.shared::cluster.b64 _, [ra];\n}\n" :: "r"(bar), "r"(cta) : "memory");
}
__device__ __forceinline__ void mbar_wait(uint32_t bar, uint32_t parity) {
  asm volatile("{\n.reg .pred p;\n.reg .u32 c;\nmov.u32 c, 0;\nLAB_WAIT:\n"
               "mbarrier.try_wait.parity.shared::cta.b64 p, [%0], %1;\n@p bra LAB_DONE;\n"
               "add.u32 c, c, 1;\nsetp.lt.u32 p, c, 200000;\n@p bra LAB_WAIT;\nLAB_DONE:\n}\n" :: "r"(bar), "r"(parity) : "memory");
}
__device__ __forceinline__ void tma_load(uint32_t dst, const CUtensorMap* tm, uint32_t bar, int c0, int c1) {
  asm volatile("cp.async.bulk.tensor.2d.shared::cluster.global.mbarrier::complete_tx::bytes [%0], [%1, {%3, %4}], [%2];"
    :: "r"(dst), "l"((uint64_t)tm), "r"(bar), "r"(c0), "r"(c1) : "memory");
}
__device__ __forceinline__ void tma_load_mc(uint32_t dst, const CUtensorMap* tm, uint32_t bar, int c0, int c1) {
  asm volatile("cp.async.bulk.tensor.2d.shared::cluster.global.mbarrier::complete_tx::bytes.multicast::cluster [%0], [%1, {%3, %4}], [%2], %5;"
    :: "r"(dst), "l"((uint64_t)tm), "r"(bar), "r"(c0), "r"(c1), "h"((uint16_t)3) : "memory");
}
__device__ __forceinline__ void bulk_load(uint32_t dst, const void* src, uint32_t bytes, uint32_t bar) {
  asm volatile("cp.async.bulk.shared::cluster.global.mbarrier::complete_tx::bytes [%0], [%1], %2, [%3];"
    :: "r"(dst), "l"((uint64_t)src), "r"(bytes), "r"(bar) : "memory");
}
__device__ __forceinline__ void tma_store(const CUtensorMap* tm, uint32_t src, int c0, int c1) {
  asm volatile("cp.async.bulk.tensor.2d.global.shared::cta.bulk_group [%0, {%2, %3}], [%1];"
    :: "l"((uint64_t)tm), "r"(src), "r"(c0), "r"(c1) : "memory");
}
__device__ __forceinline__ void bulk_commit() { asm volatile("cp.async.bulk.commit_group;" ::: "memory"); }
__device__ __forceinline__ void bulk_wait_read() { asm volatile("cp.async.bulk.wait_group.read 0;" ::: "memory"); }
__device__ __forceinline__ void bulk_wait_all() { asm volatile("cp.async.bulk.wait_group 0;" ::: "memory"); }
__device__ __forceinline__ void l2_prefetch(const void* p, uint32_t bytes) {
  asm volatile("cp.async.bulk.prefetch.L2.global [%0], %1;" :: "l"((uint64_t)p), "r"(bytes) : "memory");
}
__device__ __forceinline__ void prefetch_tmap(const CUtensorMap* tm) { asm volatile("prefetch.tensormap [%0];" :: "l"((uint64_t)tm) : "memory"); }
__device__ __forceinline__ void fence_async_smem() { asm volatile("fence.proxy.async.shared::cta;" ::: "memory"); }
__device__ __forceinline__ void fence_async_global() { asm volatile("fence.proxy.async.global;" ::: "memory"); }
__device__ __forceinline__ void wgmma_fence() { asm volatile("wgmma.fence.sync.aligned;" ::: "memory"); }
__device__ __forceinline__ void wgmma_commit() { asm volatile("wgmma.commit_group.sync.aligned;" ::: "memory"); }
template<int N> __device__ __forceinline__ void wgmma_wait() { asm volatile("wgmma.wait_group.sync.aligned %0;" :: "n"(N) : "memory"); }
__device__ __forceinline__ void cluster_sync() { asm volatile("barrier.cluster.arrive.aligned;\nbarrier.cluster.wait.aligned;" ::: "memory"); }
__device__ __forceinline__ void wg_sync(int wg) { asm volatile("bar.sync %0, 128;" :: "r"(wg + 1) : "memory"); }
__device__ __forceinline__ void stmatrix_x4(uint32_t addr, uint32_t r0, uint32_t r1, uint32_t r2, uint32_t r3) {
  asm volatile("stmatrix.sync.aligned.m8n8.x4.shared.b16 [%0], {%1, %2, %3, %4};" :: "r"(addr), "r"(r0), "r"(r1), "r"(r2), "r"(r3) : "memory");
}
__device__ __forceinline__ void stmatrix_x4_t(uint32_t addr, uint32_t r0, uint32_t r1, uint32_t r2, uint32_t r3) {
  asm volatile("stmatrix.sync.aligned.m8n8.x4.trans.shared.b16 [%0], {%1, %2, %3, %4};" :: "r"(addr), "r"(r0), "r"(r1), "r"(r2), "r"(r3) : "memory");
}
__device__ __forceinline__ void ldmatrix_x4(uint32_t addr, uint32_t& r0, uint32_t& r1, uint32_t& r2, uint32_t& r3) {
  asm volatile("ldmatrix.sync.aligned.m8n8.x4.shared.b16 {%0, %1, %2, %3}, [%4];" : "=r"(r0), "=r"(r1), "=r"(r2), "=r"(r3) : "r"(addr) : "memory");
}
__device__ __forceinline__ uint32_t pack_bf16(float lo, float hi) {
  uint32_t r; asm("cvt.rn.bf16x2.f32 %0, %1, %2;" : "=r"(r) : "f"(hi), "f"(lo)); return r;
}
__device__ __forceinline__ float bf_lo(uint32_t v) { return __uint_as_float(v << 16); }
__device__ __forceinline__ float bf_hi(uint32_t v) { return __uint_as_float(v & 0xffff0000u); }

__device__ __forceinline__ void flag_signal(int id) {
  asm volatile("red.release.gpu.global.add.s32 [%0], 1;" :: "l"(g_flags + id * 8) : "memory");
}
__device__ __forceinline__ void flag_wait(int id, int target) {
  const int* p = g_flags + id * 8;
  for (int it = 0; it < 4000000; it++) {
    int v;
    asm volatile("ld.acquire.gpu.global.s32 %0, [%1];" : "=r"(v) : "l"(p) : "memory");
    if (v >= target) break;
    __nanosleep(20);
  }
}

__device__ __forceinline__ float gelu(float v) {
  const float C1 = -2.3022081986f, C2 = -0.1029432397f;
  float t = v * fmaf(v * v, C2, C1);
  float e; asm("ex2.approx.ftz.f32 %0, %1;" : "=f"(e) : "f"(t));
  float r; asm("rcp.approx.ftz.f32 %0, %1;" : "=f"(r) : "f"(1.0f + e));
  return v * r;
}

template<int N, int TB> struct Wgmma;
template<int TB> struct Wgmma<160, TB> {
  static __device__ __forceinline__ void mma(float (&d)[80], uint64_t da, uint64_t db, int scale_d) {
    asm volatile("{\n.reg .pred p;\nsetp.ne.b32 p, %82, 0;\n"
      "wgmma.mma_async.sync.aligned.m64n160k16.f32.bf16.bf16 {%0, %1, %2, %3, %4, %5, %6, %7, %8, %9, %10, %11, %12, %13, %14, %15, %16, %17, %18, %19, %20, %21, %22, %23, %24, %25, %26, %27, %28, %29, %30, %31, %32, %33, %34, %35, %36, %37, %38, %39, %40, %41, %42, %43, %44, %45, %46, %47, %48, %49, %50, %51, %52, %53, %54, %55, %56, %57, %58, %59, %60, %61, %62, %63, %64, %65, %66, %67, %68, %69, %70, %71, %72, %73, %74, %75, %76, %77, %78, %79}, %80, %81, p, 1, 1, 0, %83;\n}\n"
      : "+f"(d[0]), "+f"(d[1]), "+f"(d[2]), "+f"(d[3]), "+f"(d[4]), "+f"(d[5]), "+f"(d[6]), "+f"(d[7]), "+f"(d[8]), "+f"(d[9]), "+f"(d[10]), "+f"(d[11]), "+f"(d[12]), "+f"(d[13]), "+f"(d[14]), "+f"(d[15]), "+f"(d[16]), "+f"(d[17]), "+f"(d[18]), "+f"(d[19]), "+f"(d[20]), "+f"(d[21]), "+f"(d[22]), "+f"(d[23]), "+f"(d[24]), "+f"(d[25]), "+f"(d[26]), "+f"(d[27]), "+f"(d[28]), "+f"(d[29]), "+f"(d[30]), "+f"(d[31]), "+f"(d[32]), "+f"(d[33]), "+f"(d[34]), "+f"(d[35]), "+f"(d[36]), "+f"(d[37]), "+f"(d[38]), "+f"(d[39]), "+f"(d[40]), "+f"(d[41]), "+f"(d[42]), "+f"(d[43]), "+f"(d[44]), "+f"(d[45]), "+f"(d[46]), "+f"(d[47]), "+f"(d[48]), "+f"(d[49]), "+f"(d[50]), "+f"(d[51]), "+f"(d[52]), "+f"(d[53]), "+f"(d[54]), "+f"(d[55]), "+f"(d[56]), "+f"(d[57]), "+f"(d[58]), "+f"(d[59]), "+f"(d[60]), "+f"(d[61]), "+f"(d[62]), "+f"(d[63]), "+f"(d[64]), "+f"(d[65]), "+f"(d[66]), "+f"(d[67]), "+f"(d[68]), "+f"(d[69]), "+f"(d[70]), "+f"(d[71]), "+f"(d[72]), "+f"(d[73]), "+f"(d[74]), "+f"(d[75]), "+f"(d[76]), "+f"(d[77]), "+f"(d[78]), "+f"(d[79])
      : "l"(da), "l"(db), "r"(scale_d), "n"(TB));
  }
};
template<int TB> struct Wgmma<192, TB> {
  static __device__ __forceinline__ void mma(float (&d)[96], uint64_t da, uint64_t db, int scale_d) {
    asm volatile("{\n.reg .pred p;\nsetp.ne.b32 p, %98, 0;\n"
      "wgmma.mma_async.sync.aligned.m64n192k16.f32.bf16.bf16 {%0, %1, %2, %3, %4, %5, %6, %7, %8, %9, %10, %11, %12, %13, %14, %15, %16, %17, %18, %19, %20, %21, %22, %23, %24, %25, %26, %27, %28, %29, %30, %31, %32, %33, %34, %35, %36, %37, %38, %39, %40, %41, %42, %43, %44, %45, %46, %47, %48, %49, %50, %51, %52, %53, %54, %55, %56, %57, %58, %59, %60, %61, %62, %63, %64, %65, %66, %67, %68, %69, %70, %71, %72, %73, %74, %75, %76, %77, %78, %79, %80, %81, %82, %83, %84, %85, %86, %87, %88, %89, %90, %91, %92, %93, %94, %95}, %96, %97, p, 1, 1, 0, %99;\n}\n"
      : "+f"(d[0]), "+f"(d[1]), "+f"(d[2]), "+f"(d[3]), "+f"(d[4]), "+f"(d[5]), "+f"(d[6]), "+f"(d[7]), "+f"(d[8]), "+f"(d[9]), "+f"(d[10]), "+f"(d[11]), "+f"(d[12]), "+f"(d[13]), "+f"(d[14]), "+f"(d[15]), "+f"(d[16]), "+f"(d[17]), "+f"(d[18]), "+f"(d[19]), "+f"(d[20]), "+f"(d[21]), "+f"(d[22]), "+f"(d[23]), "+f"(d[24]), "+f"(d[25]), "+f"(d[26]), "+f"(d[27]), "+f"(d[28]), "+f"(d[29]), "+f"(d[30]), "+f"(d[31]), "+f"(d[32]), "+f"(d[33]), "+f"(d[34]), "+f"(d[35]), "+f"(d[36]), "+f"(d[37]), "+f"(d[38]), "+f"(d[39]), "+f"(d[40]), "+f"(d[41]), "+f"(d[42]), "+f"(d[43]), "+f"(d[44]), "+f"(d[45]), "+f"(d[46]), "+f"(d[47]), "+f"(d[48]), "+f"(d[49]), "+f"(d[50]), "+f"(d[51]), "+f"(d[52]), "+f"(d[53]), "+f"(d[54]), "+f"(d[55]), "+f"(d[56]), "+f"(d[57]), "+f"(d[58]), "+f"(d[59]), "+f"(d[60]), "+f"(d[61]), "+f"(d[62]), "+f"(d[63]), "+f"(d[64]), "+f"(d[65]), "+f"(d[66]), "+f"(d[67]), "+f"(d[68]), "+f"(d[69]), "+f"(d[70]), "+f"(d[71]), "+f"(d[72]), "+f"(d[73]), "+f"(d[74]), "+f"(d[75]), "+f"(d[76]), "+f"(d[77]), "+f"(d[78]), "+f"(d[79]), "+f"(d[80]), "+f"(d[81]), "+f"(d[82]), "+f"(d[83]), "+f"(d[84]), "+f"(d[85]), "+f"(d[86]), "+f"(d[87]), "+f"(d[88]), "+f"(d[89]), "+f"(d[90]), "+f"(d[91]), "+f"(d[92]), "+f"(d[93]), "+f"(d[94]), "+f"(d[95])
      : "l"(da), "l"(db), "r"(scale_d), "n"(TB));
  }
};

__device__ __forceinline__ uint64_t make_desc(uint32_t addr, uint32_t lbo, uint32_t sbo) {
  return (uint64_t)((addr & 0x3FFFF) >> 4) | ((uint64_t)(lbo >> 4) << 16) | ((uint64_t)(sbo >> 4) << 32) | ((uint64_t)1 << 62);
}

struct Ctx {
  uint32_t base;
  uint32_t full0, empty0, sfree, z1rdy, turn0;
  int warp, lane;
};

__device__ __forceinline__ void release_stage(const Ctx& c, int it) {
  if (c.lane < 2) mbar_arrive_cluster(c.empty0 + 8 * (it & (STAGES - 1)), c.lane);
}

template<int N, int TB>
__device__ __forceinline__ void mainloop(const Ctx& c, float (&acc)[2][N / 2], int it0, int n, bool zero_init, bool pend, uint32_t pass_bar) {
  for (int k = 0; k < n; k++) {
    int it = it0 + k, s = it & (STAGES - 1);
    mbar_wait(c.full0 + 8 * s, (it / STAGES) & 1);
    if (pass_bar && k == n - 1 && c.lane == 0 && c.warp == 0) mbar_arrive(pass_bar);
    uint32_t sa = c.base + s * STAGE_BYTES;
    uint64_t da = make_desc(sa, 16, 1024);
    uint64_t db = TB == 0 ? make_desc(sa + A_BYTES, 16, 1024) : make_desc(sa + A_BYTES, 8192, 1024);
    wgmma_fence();
    #pragma unroll
    for (int kk = 0; kk < 4; kk++) {
      int sd = (zero_init && k == 0 && kk == 0) ? 0 : 1;
      #pragma unroll
      for (int mb = 0; mb < 2; mb++)
        Wgmma<N, TB>::mma(acc[mb], da + (uint64_t)(mb * 512 + kk * 2), db + (uint64_t)(TB == 0 ? kk * 2 : kk * 128), sd);
    }
    wgmma_commit();
    if (k > 0 || pend) { wgmma_wait<1>(); release_stage(c, it - 1); }
  }
}
template<int N>
__device__ __forceinline__ void fence_acc(float (&acc)[2][N / 2]) {
  #pragma unroll
  for (int mb = 0; mb < 2; mb++)
    #pragma unroll
    for (int e = 0; e < N / 2; e++) asm volatile("" : "+f"(acc[mb][e]) :: "memory");
}
template<int N>
__device__ __forceinline__ void drain(const Ctx& c, float (&acc)[2][N / 2], int it_last) {
  wgmma_wait<0>();
  fence_acc<N>(acc);
  release_stage(c, it_last);
}

template<int N>
__device__ __forceinline__ void apply_ln(const Ctx& c, float (&acc)[2][N / 2], int row0, const float* cs, float sgn) {
  float2 rs[2][2];
  #pragma unroll
  for (int mb = 0; mb < 2; mb++)
    #pragma unroll
    for (int hh = 0; hh < 2; hh++) {
      rs[mb][hh] = __ldcg(&g_rowstat[row0 + mb * 64 + c.warp * 16 + hh * 8 + (c.lane >> 2)]);
      rs[mb][hh].y *= sgn;
      rs[mb][hh].x *= -rs[mb][hh].y;
    }
  #pragma unroll
  for (int j = 0; j < N / 8; j++) {
    float2 s2 = __ldcg((const float2*)(cs + 8 * j + 2 * (c.lane & 3)));
    #pragma unroll
    for (int mb = 0; mb < 2; mb++) {
      acc[mb][4 * j + 0] = fmaf(acc[mb][4 * j + 0], rs[mb][0].y, rs[mb][0].x * s2.x);
      acc[mb][4 * j + 1] = fmaf(acc[mb][4 * j + 1], rs[mb][0].y, rs[mb][0].x * s2.y);
      acc[mb][4 * j + 2] = fmaf(acc[mb][4 * j + 2], rs[mb][1].y, rs[mb][1].x * s2.x);
      acc[mb][4 * j + 3] = fmaf(acc[mb][4 * j + 3], rs[mb][1].y, rs[mb][1].x * s2.y);
    }
  }
}

template<int N>
__device__ __forceinline__ void stage_transposed(const Ctx& c, float (&acc)[2][N / 2]) {
  int mi = c.lane >> 3, r = c.lane & 7;
  uint32_t a0 = c.base + SBUF_OFF + ((mi >> 1) * 8 + r) * 128 + (((2 * c.warp + (mi & 1)) ^ r) << 4);
  #pragma unroll
  for (int mb = 0; mb < 2; mb++)
    #pragma unroll
    for (int j = 0; j < N / 8; j += 2)
      stmatrix_x4_t(a0 + mb * (N * 128) + j * 1024,
                    pack_bf16(acc[mb][4 * j + 0], acc[mb][4 * j + 1]), pack_bf16(acc[mb][4 * j + 2], acc[mb][4 * j + 3]),
                    pack_bf16(acc[mb][4 * j + 4], acc[mb][4 * j + 5]), pack_bf16(acc[mb][4 * j + 6], acc[mb][4 * j + 7]));
}

__device__ __forceinline__ float quad_sum(float v) {
  v += __shfl_xor_sync(0xffffffffu, v, 1);
  v += __shfl_xor_sync(0xffffffffu, v, 2);
  return v;
}
__device__ __forceinline__ float sum8(uint4 v) {
  return ((bf_lo(v.x) + bf_hi(v.x)) + (bf_lo(v.y) + bf_hi(v.y))) + ((bf_lo(v.z) + bf_hi(v.z)) + (bf_lo(v.w) + bf_hi(v.w)));
}
__device__ __forceinline__ float sq8(uint4 v, float m) {
  float a0 = bf_lo(v.x) - m, a1 = bf_hi(v.x) - m, a2 = bf_lo(v.y) - m, a3 = bf_hi(v.y) - m;
  float a4 = bf_lo(v.z) - m, a5 = bf_hi(v.z) - m, a6 = bf_lo(v.w) - m, a7 = bf_hi(v.w) - m;
  return ((a0 * a0 + a1 * a1) + (a2 * a2 + a3 * a3)) + ((a4 * a4 + a5 * a5) + (a6 * a6 + a7 * a7));
}

__device__ __forceinline__ void prepass(const Ctx& c, int tid, const __nv_bfloat16* x, const __nv_bfloat16* hre,
                                        const __nv_bfloat16* him, const __nv_bfloat16* win, float* red) {
  int cta = blockIdx.x;
  int sub = tid & 7, grp = tid >> 3;
  uint4 vx[10], vh[10], vw[10];
  const uint4* px = (const uint4*)(x + (size_t)(cta * 16 + grp) * DM) + sub;
  #pragma unroll
  for (int i = 0; i < 10; i++) vx[i] = __ldg(px + 8 * i);
  int hr = cta * 10 + grp;
  bool do_h = grp < 10;
  const uint4* ph = (const uint4*)((hr < DM ? hre : him) + (size_t)(hr < DM ? hr : hr - DM) * DM) + sub;
  #pragma unroll
  for (int i = 0; i < 10; i++) vh[i] = do_h ? __ldg(ph + 8 * i) : make_uint4(0, 0, 0, 0);
  bool do_w = cta < 96;
  const uint4* pw = (const uint4*)(win + (size_t)(tid >> 1) * (2 * FH) + cta * 16) + (tid & 1);
  #pragma unroll
  for (int i = 0; i < 10; i++) vw[i] = do_w ? __ldg(pw + (size_t)i * 64 * (2 * FH / 8)) : make_uint4(0, 0, 0, 0);
  float s = 0.f;
  #pragma unroll
  for (int i = 0; i < 10; i++) s += sum8(vx[i]);
  s += __shfl_xor_sync(0xffffffffu, s, 1); s += __shfl_xor_sync(0xffffffffu, s, 2); s += __shfl_xor_sync(0xffffffffu, s, 4);
  float mean = s * (1.0f / DM), q = 0.f;
  #pragma unroll
  for (int i = 0; i < 10; i++) q += sq8(vx[i], mean);
  q += __shfl_xor_sync(0xffffffffu, q, 1); q += __shfl_xor_sync(0xffffffffu, q, 2); q += __shfl_xor_sync(0xffffffffu, q, 4);
  if (sub == 0) g_rowstat[cta * 16 + grp] = make_float2(mean, rsqrtf(q * (1.0f / DM) + LN_EPS));
  float hs = 0.f;
  #pragma unroll
  for (int i = 0; i < 10; i++) hs += sum8(vh[i]);
  hs += __shfl_xor_sync(0xffffffffu, hs, 1); hs += __shfl_xor_sync(0xffffffffu, hs, 2); hs += __shfl_xor_sync(0xffffffffu, hs, 4);
  if (sub == 0 && do_h) g_colsum[hr] = hs;
  float w[8];
  #pragma unroll
  for (int e = 0; e < 8; e++) w[e] = 0.f;
  #pragma unroll
  for (int i = 0; i < 10; i++) {
    w[0] += bf_lo(vw[i].x); w[1] += bf_hi(vw[i].x); w[2] += bf_lo(vw[i].y); w[3] += bf_hi(vw[i].y);
    w[4] += bf_lo(vw[i].z); w[5] += bf_hi(vw[i].z); w[6] += bf_lo(vw[i].w); w[7] += bf_hi(vw[i].w);
  }
  #pragma unroll
  for (int e = 0; e < 8; e++) {
    #pragma unroll
    for (int o = 2; o < 32; o <<= 1) w[e] += __shfl_xor_sync(0xffffffffu, w[e], o);
  }
  if (c.lane < 2) {
    #pragma unroll
    for (int e = 0; e < 8; e++) red[c.warp * 16 + c.lane * 8 + e] = w[e];
  }
  wg_sync(1);
  if (tid < 16 && do_w) g_colsum[1280 + cta * 16 + tid] = (red[tid] + red[16 + tid]) + (red[32 + tid] + red[48 + tid]);
  __threadfence();
  wg_sync(1);
  if (tid == 0) flag_signal(FL_PRE);
}

__device__ __forceinline__ void wg_flag_wait(int wg, int tid, int id, int target) {
  if (tid == 0) flag_wait(id, target);
  wg_sync(wg);
}

__device__ __forceinline__ void take_ticket() {
  int t = atomicAdd(&g_flags[FL_TICKET * 8], 1);
  if (t == NCTA - 1) {
    for (int i = 0; i < FL_COUNT; i++) g_flags[i * 8] = 0;
  }
}

__global__ void __cluster_dims__(2, 1, 1) __launch_bounds__(384, 1)
fused_kernel(const __grid_constant__ Maps maps, const __nv_bfloat16* __restrict__ x, const __nv_bfloat16* __restrict__ hre,
             const __nv_bfloat16* __restrict__ him, const __nv_bfloat16* __restrict__ win, const __nv_bfloat16* __restrict__ sre,
             const __nv_bfloat16* __restrict__ sim, const __nv_bfloat16* __restrict__ wsp, const __nv_bfloat16* __restrict__ bsp,
             const __nv_bfloat16* __restrict__ wout) {
  extern __shared__ uint8_t smem_raw[];
  Ctx c;
  c.base = (smem_u32(smem_raw) + 1023) & ~1023u;
  c.full0 = c.base + BAR_OFF; c.empty0 = c.full0 + 8 * STAGES; c.sfree = c.empty0 + 8 * STAGES; c.z1rdy = c.sfree + 8; c.turn0 = c.z1rdy + 8;
  const int wg = __shfl_sync(0xffffffffu, threadIdx.x >> 7, 0), tid = threadIdx.x & 127;
  c.warp = __shfl_sync(0xffffffffu, tid >> 5, 0); c.lane = tid & 31;
  const int rank = blockIdx.x & 1, pair = blockIdx.x >> 1;
  const bool isG = pair & 1;
  const int q = pair >> 1, rb = q >> 1, ct = (q & 1) * 2 + rank;
  const int row0 = rb * 128;

  if (threadIdx.x == 0) { TSTAMP(0); TSTAMP_G(30); }
  if (threadIdx.x == 0) {
    for (int s = 0; s < STAGES; s++) { mbar_init(c.full0 + 8 * s, 1); mbar_init(c.empty0 + 8 * s, 8); }
    mbar_init(c.sfree, 1); mbar_init(c.z1rdy, 128); mbar_init(c.turn0, 1); mbar_init(c.turn0 + 8, 1);
    asm volatile("fence.mbarrier_init.release.cluster;" ::: "memory");
  }
  __syncthreads();
  cluster_sync();
  if (threadIdx.x == 0) TSTAMP(1);

  if (wg == 2) {
    asm volatile("setmaxnreg.dec.sync.aligned.u32 40;");
    if (tid == 0) {
      int it = 0;
      uint32_t sa = 0, fb = 0;
      auto acquire = [&](uint32_t bytes) {
        int s = it & (STAGES - 1);
        mbar_wait(c.empty0 + 8 * s, ((it / STAGES) & 1) ^ 1);
        sa = c.base + s * STAGE_BYTES; fb = c.full0 + 8 * s;
        mbar_expect_tx(fb, bytes);
        it++;
      };
      auto loadA = [&](const CUtensorMap* tm, int kc) { tma_load_mc(sa + rank * 8192, tm, fb, kc, row0 + rank * 64); };
      if (!isG) {
        for (int t = 0; t < 2; t++)
          for (int k = 0; k < 10; k++) {
            acquire(A_BYTES + 160 * 128);
            loadA(&maps.x, k * 64);
            tma_load(sa + A_BYTES, t == 0 ? &maps.hre : &maps.him, fb, k * 64, ct * 160);
          }
        for (int kk = 0; kk < 64 - JSPLIT; kk++) {
          acquire(A_BYTES + 160 * 128);
          loadA(kk < 32 ? &maps.sre : &maps.sim, (kk & 31) * 64);
          if ((kk & 31) == 0) { TSTAMP(22 + (kk >> 5) * 2); flag_wait(FL_AB + (kk >> 5) * 4 + ct, 16); fence_async_global(); TSTAMP(23 + (kk >> 5) * 2); }
          tma_load(sa + A_BYTES, &maps.abT, fb, kk * 64, ct * 160);
        }
        take_ticket();
      } else {
        for (int t = 0; t < 2; t++)
          for (int k = 0; k < 10; k++) {
            acquire(A_BYTES + 192 * 128);
            loadA(&maps.x, k * 64);
            int n0 = (t == 0 ? FH : 0) + ct * 192;
            for (int b = 0; b < 3; b++) tma_load(sa + A_BYTES + b * 8192, &maps.win, fb, n0 + b * 64, k * 64);
          }
        for (int k = 0; k < 32; k++) {
          acquire(A_BYTES + 192 * 128);
          loadA(&maps.wsp, k * 64);
          if (k == 0) { TSTAMP(22); flag_wait(FL_Z2N + ct, 16); fence_async_global(); TSTAMP(23); }
          tma_load(sa + A_BYTES, &maps.z2nT, fb, k * 64, ct * 192);
        }
        flag_wait(FL_AB + 4 + ct, 16); fence_async_global();
        for (int kk = 64 - JSPLIT; kk < 64; kk++) {
          acquire(A_BYTES + 160 * 128);
          loadA(&maps.sim, (kk & 31) * 64);
          tma_load(sa + A_BYTES, &maps.abT, fb, kk * 64, ct * 160);
        }
        for (int k = 0; k < 12; k++) {
          acquire(A_BYTES + 192 * 128);
          for (int b = 0; b < 3; b++) tma_load(sa + A_BYTES + b * 8192, &maps.wout, fb, ct * 160 + b * 64, k * 64);
          if (k == 0) { TSTAMP(24); flag_wait(FL_H + rb, 4); fence_async_global(); TSTAMP(25); }
          loadA(&maps.h, k * 64);
        }
        for (int p = 0; p < 2; p++) {
          acquire(STAGE_BYTES);
          if (p == 0) { TSTAMP(26); flag_wait(FL_PART + rb * 4 + ct, 1); fence_async_global(); TSTAMP(27); }
          bulk_load(sa, g_part + ((size_t)(rb * 4 + ct) * 40 + p * 20) * 128, STAGE_BYTES, fb);
        }
        take_ticket();
      }
    } else if (c.warp == 1) {
      __nanosleep(1500);
      int r = row0 + ct * 32 + c.lane;
      if (!isG) {
        for (int sgm = 0; sgm < 4; sgm++) l2_prefetch(sre + (size_t)r * SEQ + sgm * 512, 1024);
        __nanosleep(3000);
        for (int sgm = 0; sgm < 4; sgm++) l2_prefetch(sim + (size_t)r * SEQ + sgm * 512, 1024);
      } else {
        for (int sgm = 0; sgm < 4; sgm++) l2_prefetch(wsp + (size_t)r * SEQ + sgm * 512, 1024);
        if (c.lane < 12) l2_prefetch(wout + (size_t)((rb * 4 + ct) * 12 + c.lane) * DM, DM * 2);
      }
    }
  } else {
    asm volatile("setmaxnreg.inc.sync.aligned.u32 232;");
    const uint32_t sbuf = c.base + SBUF_OFF;
    if (wg == 1) prepass(c, tid, x, hre, him, win, (float*)(smem_raw + (c.base - smem_u32(smem_raw)) + BAR_OFF + 256));
    if (wg == 1) TSTAMP(2);
    if (!isG) {
      {
        float acc[2][80];
        if (wg == 1) mbar_wait(c.turn0 + 8, 0);
        mainloop<160, 0>(c, acc, wg * 10, 10, true, false, c.turn0 + 8 * (wg ^ 1));
        drain<160>(c, acc, wg * 10 + 9);
        TSTAMP(4 + wg * 4);
        wg_flag_wait(wg, tid, FL_PRE, NCTA);
        TSTAMP(5 + wg * 4);
        apply_ln<160>(c, acc, row0, g_colsum + wg * DM + ct * 160, wg == 0 ? 1.0f : -1.0f);
        if (wg == 1) mbar_wait(c.sfree, 0);
        stage_transposed<160>(c, acc);
        fence_async_smem();
        wg_sync(wg);
        if (tid == 0) {
          TSTAMP(6 + wg * 4);
          tma_store(&maps.abT, sbuf, wg * SEQ + row0, ct * 160);
          tma_store(&maps.abT, sbuf + 160 * 128, wg * SEQ + row0 + 64, ct * 160);
          bulk_commit();
          bulk_wait_all();
          if (wg == 0) mbar_arrive(c.sfree);
          fence_async_global();
          flag_signal(FL_AB + wg * 4 + ct);
          TSTAMP(7 + wg * 4);
        }
      }
      if (wg == 0) {
        float acc[2][80];
        #pragma unroll
        for (int mb = 0; mb < 2; mb++)
          #pragma unroll
          for (int hh = 0; hh < 2; hh++) {
            const uint32_t* px = (const uint32_t*)(x + (size_t)(row0 + mb * 64 + c.warp * 16 + hh * 8 + (c.lane >> 2)) * DM + ct * 160) + (c.lane & 3);
            #pragma unroll
            for (int j = 0; j < 20; j++) {
              uint32_t v = __ldg(px + 4 * j);
              acc[mb][4 * j + 2 * hh] = bf_lo(v); acc[mb][4 * j + 2 * hh + 1] = bf_hi(v);
            }
          }
        fence_acc<160>(acc);
        mbar_wait(c.turn0, 0);
        TSTAMP(12);
        mainloop<160, 0>(c, acc, 20, 64 - JSPLIT, false, false, 0);
        drain<160>(c, acc, 20 + 64 - JSPLIT - 1);
        TSTAMP(13);
        float4* pp = g_part + (size_t)(rb * 4 + ct) * 40 * 128 + tid;
        #pragma unroll
        for (int mb = 0; mb < 2; mb++)
          #pragma unroll
          for (int j = 0; j < 20; j++)
            __stcg(pp + (mb * 20 + j) * 128, make_float4(acc[mb][4 * j], acc[mb][4 * j + 1], acc[mb][4 * j + 2], acc[mb][4 * j + 3]));
        __threadfence();
        wg_sync(0);
        if (tid == 0) flag_signal(FL_PART + rb * 4 + ct);
        TSTAMP(14);
      }
    } else if (wg == 0) {
      {
        float acc[2][96];
        mainloop<192, 1>(c, acc, 0, 10, true, false, c.turn0 + 8);
        drain<192>(c, acc, 9);
        TSTAMP(4);
        wg_flag_wait(0, tid, FL_PRE, NCTA);
        TSTAMP(5);
        apply_ln<192>(c, acc, row0, g_colsum + 1280 + FH + ct * 192, 1.0f);
        float sm[2][2];
        #pragma unroll
        for (int mb = 0; mb < 2; mb++) {
          float s0 = 0.f, s1 = 0.f;
          #pragma unroll
          for (int j = 0; j < 24; j++) {
            #pragma unroll
            for (int e = 0; e < 4; e++) acc[mb][4 * j + e] = gelu(acc[mb][4 * j + e]);
            s0 += acc[mb][4 * j] + acc[mb][4 * j + 1];
            s1 += acc[mb][4 * j + 2] + acc[mb][4 * j + 3];
          }
          sm[mb][0] = quad_sum(s0) * (1.0f / 192); sm[mb][1] = quad_sum(s1) * (1.0f / 192);
        }
        #pragma unroll
        for (int mb = 0; mb < 2; mb++) {
          float q0 = 0.f, q1 = 0.f;
          #pragma unroll
          for (int j = 0; j < 24; j++) {
            float d0 = acc[mb][4 * j] - sm[mb][0], d1 = acc[mb][4 * j + 1] - sm[mb][0];
            float d2 = acc[mb][4 * j + 2] - sm[mb][1], d3 = acc[mb][4 * j + 3] - sm[mb][1];
            q0 = fmaf(d0, d0, q0); q0 = fmaf(d1, d1, q0); q1 = fmaf(d2, d2, q1); q1 = fmaf(d3, d3, q1);
          }
          q0 = quad_sum(q0); q1 = quad_sum(q1);
          if ((c.lane & 3) == 0) {
            int r = row0 + mb * 64 + c.warp * 16 + (c.lane >> 2);
            __stcg(&g_z2stat[r * 4 + ct], make_float2(sm[mb][0], q0));
            __stcg(&g_z2stat[(r + 8) * 4 + ct], make_float2(sm[mb][1], q1));
          }
        }
        __threadfence();
        wg_sync(0);
        TSTAMP(16);
        if (tid == 0) { flag_signal(FL_Z2S + rb); flag_wait(FL_Z2S + rb, 4); }
        TSTAMP(17);
        wg_sync(0);
        #pragma unroll
        for (int mb = 0; mb < 2; mb++)
          #pragma unroll
          for (int hh = 0; hh < 2; hh++) {
            int r = row0 + mb * 64 + c.warp * 16 + hh * 8 + (c.lane >> 2);
            float4 p0 = __ldcg((const float4*)&g_z2stat[r * 4]), p1 = __ldcg((const float4*)&g_z2stat[r * 4 + 2]);
            float mean = 0.25f * ((p0.x + p0.z) + (p1.x + p1.z));
            float d0 = p0.x - mean, d1 = p0.z - mean, d2 = p1.x - mean, d3 = p1.z - mean;
            float m2 = ((p0.y + p0.w) + (p1.y + p1.w)) + 192.0f * ((d0 * d0 + d1 * d1) + (d2 * d2 + d3 * d3));
            float rstd = rsqrtf(m2 * (1.0f / FH) + LN_EPS), off = -mean * rstd;
            #pragma unroll
            for (int j = 0; j < 24; j++) {
              acc[mb][4 * j + 2 * hh] = fmaf(acc[mb][4 * j + 2 * hh], rstd, off);
              acc[mb][4 * j + 2 * hh + 1] = fmaf(acc[mb][4 * j + 2 * hh + 1], rstd, off);
            }
          }
        stage_transposed<192>(c, acc);
        fence_async_smem();
        wg_sync(0);
        if (tid == 0) {
          TSTAMP(6);
          tma_store(&maps.z2nT, sbuf, row0, ct * 192);
          tma_store(&maps.z2nT, sbuf + 192 * 128, row0 + 64, ct * 192);
          bulk_commit();
          bulk_wait_all();
          mbar_arrive(c.sfree);
          fence_async_global();
          flag_signal(FL_Z2N + ct);
          TSTAMP(7);
        }
      }
      {
        float acc[2][96];
        #pragma unroll
        for (int mb = 0; mb < 2; mb++)
          #pragma unroll
          for (int hh = 0; hh < 2; hh++) {
            float b = __bfloat162float(bsp[row0 + mb * 64 + c.warp * 16 + hh * 8 + (c.lane >> 2)]);
            #pragma unroll
            for (int j = 0; j < 24; j++) { acc[mb][4 * j + 2 * hh] = b; acc[mb][4 * j + 2 * hh + 1] = b; }
          }
        fence_acc<192>(acc);
        mbar_wait(c.turn0, 0);
        TSTAMP(12);
        mainloop<192, 0>(c, acc, 20, 32, false, false, c.turn0 + 8);
        drain<192>(c, acc, 51);
        TSTAMP(13);
        mbar_wait(c.z1rdy, 0);
        int mi = c.lane >> 3, r = c.lane & 7;
        #pragma unroll
        for (int mb = 0; mb < 2; mb++)
          #pragma unroll
          for (int j = 0; j < 24; j += 2) {
            uint32_t ad = sbuf + (j >> 3) * 16384 + (mb * 64 + c.warp * 16 + (mi & 1) * 8 + r) * 128 + ((((j & 7) + (mi >> 1)) ^ r) << 4);
            uint32_t z0, z1, z2, z3;
            ldmatrix_x4(ad, z0, z1, z2, z3);
            stmatrix_x4(ad, pack_bf16(acc[mb][4 * j + 0] * bf_lo(z0), acc[mb][4 * j + 1] * bf_hi(z0)),
                            pack_bf16(acc[mb][4 * j + 2] * bf_lo(z1), acc[mb][4 * j + 3] * bf_hi(z1)),
                            pack_bf16(acc[mb][4 * j + 4] * bf_lo(z2), acc[mb][4 * j + 5] * bf_hi(z2)),
                            pack_bf16(acc[mb][4 * j + 6] * bf_lo(z3), acc[mb][4 * j + 7] * bf_hi(z3)));
          }
        fence_async_smem();
        wg_sync(0);
        if (tid == 0) {
          for (int b = 0; b < 3; b++)
            for (int hf = 0; hf < 2; hf++)
              tma_store(&maps.h, sbuf + b * 16384 + hf * 8192, ct * 192 + b * 64, row0 + hf * 64);
          bulk_commit();
          bulk_wait_all();
          mbar_arrive(c.sfree);
          fence_async_global();
          flag_signal(FL_H + rb);
          TSTAMP(14);
        }
      }
    } else {
      {
        float acc[2][96];
        mbar_wait(c.turn0 + 8, 0);
        mainloop<192, 1>(c, acc, 10, 10, true, false, c.turn0);
        drain<192>(c, acc, 19);
        TSTAMP(8);
        wg_flag_wait(1, tid, FL_PRE, NCTA);
        apply_ln<192>(c, acc, row0, g_colsum + 1280 + ct * 192, 1.0f);
        mbar_wait(c.sfree, 0);
        int mi = c.lane >> 3, r = c.lane & 7;
        #pragma unroll
        for (int mb = 0; mb < 2; mb++)
          #pragma unroll
          for (int j = 0; j < 24; j += 2) {
            uint32_t ad = sbuf + (j >> 3) * 16384 + (mb * 64 + c.warp * 16 + (mi & 1) * 8 + r) * 128 + ((((j & 7) + (mi >> 1)) ^ r) << 4);
            stmatrix_x4(ad, pack_bf16(gelu(acc[mb][4 * j + 0]), gelu(acc[mb][4 * j + 1])),
                            pack_bf16(gelu(acc[mb][4 * j + 2]), gelu(acc[mb][4 * j + 3])),
                            pack_bf16(gelu(acc[mb][4 * j + 4]), gelu(acc[mb][4 * j + 5])),
                            pack_bf16(gelu(acc[mb][4 * j + 6]), gelu(acc[mb][4 * j + 7])));
          }
        mbar_arrive(c.z1rdy);
        TSTAMP(11);
      }
      {
        float acc[2][80];
        mbar_wait(c.turn0 + 8, 1);
        mainloop<160, 0>(c, acc, 52, JSPLIT, true, false, 0);
        TSTAMP(18);
        mainloop<160, 1>(c, acc, 52 + JSPLIT, 12, false, true, 0);
        drain<160>(c, acc, 52 + JSPLIT + 11);
        TSTAMP(19);
        mbar_wait(c.sfree, 1);
        int mi = c.lane >> 3, r = c.lane & 7;
        #pragma unroll
        for (int mb = 0; mb < 2; mb++) {
          const int it = 52 + JSPLIT + 12 + mb, s = it & (STAGES - 1);
          mbar_wait(c.full0 + 8 * s, (it / STAGES) & 1);
          const float4* pp = (const float4*)(smem_raw + (c.base - smem_u32(smem_raw)) + s * STAGE_BYTES) + tid;
          int row = mb * 64 + c.warp * 16 + (mi & 1) * 8 + r;
          #pragma unroll
          for (int j = 0; j < 20; j += 2) {
            float4 p0 = pp[j * 128], p1 = pp[(j + 1) * 128];
            uint32_t ad = sbuf + (j >> 2) * 8192 + row * 64 + ((((j & 3) + (mi >> 1)) ^ ((row >> 1) & 3)) << 4);
            stmatrix_x4(ad, pack_bf16(acc[mb][4 * j + 0] + p0.x, acc[mb][4 * j + 1] + p0.y),
                            pack_bf16(acc[mb][4 * j + 2] + p0.z, acc[mb][4 * j + 3] + p0.w),
                            pack_bf16(acc[mb][4 * j + 4] + p1.x, acc[mb][4 * j + 5] + p1.y),
                            pack_bf16(acc[mb][4 * j + 6] + p1.z, acc[mb][4 * j + 7] + p1.w));
          }
        }
        fence_async_smem();
        wg_sync(1);
        if (tid == 0) {
          for (int b = 0; b < 5; b++) tma_store(&maps.out, sbuf + b * 8192, ct * 160 + b * 32, row0);
          bulk_commit();
          bulk_wait_read();
        }
        TSTAMP(20);
      }
    }
  }
  cluster_sync();
  if (threadIdx.x == 0) { TSTAMP(21); TSTAMP_G(31); }
}

typedef CUresult (*EncodeFn)(CUtensorMap*, CUtensorMapDataType, cuuint32_t, void*, const cuuint64_t*, const cuuint64_t*,
                             const cuuint32_t*, const cuuint32_t*, CUtensorMapInterleave, CUtensorMapSwizzle,
                             CUtensorMapL2promotion, CUtensorMapFloatOOBfill);

void make_map(EncodeFn enc, CUtensorMap* m, const void* p, int rows, int cols, int box_rows, int box_cols, CUtensorMapSwizzle sw) {
  cuuint64_t gd[2] = {(cuuint64_t)cols, (cuuint64_t)rows};
  cuuint64_t gs[1] = {(cuuint64_t)cols * 2};
  cuuint32_t bd[2] = {(cuuint32_t)box_cols, (cuuint32_t)box_rows};
  cuuint32_t es[2] = {1, 1};
  enc(m, CU_TENSOR_MAP_DATA_TYPE_BFLOAT16, 2, (void*)p, gd, gs, bd, es, CU_TENSOR_MAP_INTERLEAVE_NONE, sw,
      CU_TENSOR_MAP_L2_PROMOTION_L2_256B, CU_TENSOR_MAP_FLOAT_OOB_FILL_NONE);
}

}

extern "C" void kernel_launch(void* const* d_in, const int* in_sizes, int n_in, void* d_out, int out_size) {
  const __nv_bfloat16* x = (const __nv_bfloat16*)d_in[0];
  const __nv_bfloat16* sre = (const __nv_bfloat16*)d_in[1];
  const __nv_bfloat16* sim = (const __nv_bfloat16*)d_in[2];
  const __nv_bfloat16* hre = (const __nv_bfloat16*)d_in[3];
  const __nv_bfloat16* him = (const __nv_bfloat16*)d_in[4];
  const __nv_bfloat16* win = (const __nv_bfloat16*)d_in[6];
  const __nv_bfloat16* wsp = (const __nv_bfloat16*)d_in[7];
  const __nv_bfloat16* bsp = (const __nv_bfloat16*)d_in[8];
  const __nv_bfloat16* wout = (const __nv_bfloat16*)d_in[9];

  void* fn = nullptr;
  cudaDriverEntryPointQueryResult qr;
  cudaGetDriverEntryPoint("cuTensorMapEncodeTiled", &fn, cudaEnableDefault, &qr);
  EncodeFn enc = (EncodeFn)fn;
  void *p_abT, *p_z2nT, *p_h;
  cudaGetSymbolAddress(&p_abT, g_abT);
  cudaGetSymbolAddress(&p_z2nT, g_z2nT);
  cudaGetSymbolAddress(&p_h, g_h);
  Maps m;
  const CUtensorMapSwizzle S128 = CU_TENSOR_MAP_SWIZZLE_128B;
  make_map(enc, &m.x, x, SEQ, DM, 64, 64, S128);
  make_map(enc, &m.hre, hre, DM, DM, 160, 64, S128);
  make_map(enc, &m.him, him, DM, DM, 160, 64, S128);
  make_map(enc, &m.win, win, DM, 2 * FH, 64, 64, S128);
  make_map(enc, &m.sre, sre, SEQ, SEQ, 64, 64, S128);
  make_map(enc, &m.sim, sim, SEQ, SEQ, 64, 64, S128);
  make_map(enc, &m.wsp, wsp, SEQ, SEQ, 64, 64, S128);
  make_map(enc, &m.abT, p_abT, DM, 2 * SEQ, 160, 64, S128);
  make_map(enc, &m.z2nT, p_z2nT, FH, SEQ, 192, 64, S128);
  make_map(enc, &m.h, p_h, SEQ, FH, 64, 64, S128);
  make_map(enc, &m.wout, wout, FH, DM, 64, 64, S128);
  make_map(enc, &m.out, d_out, SEQ, DM, 128, 32, CU_TENSOR_MAP_SWIZZLE_64B);
  cudaFuncSetAttribute(fused_kernel, cudaFuncAttributeMaxDynamicSharedMemorySize, SMEM_BYTES);
  fused_kernel<<<NCTA, 384, SMEM_BYTES>>>(m, x, hre, him, win, sre, sim, wsp, bsp, wout);
}
```

```cpp
#include <cuda.h>
#include <cuda_runtime.h>
#include <cuda_bf16.h>
#include <stdint.h>

namespace {

constexpr int SEQ = 2048, DM = 640, FH = 768;
constexpr int STAGES = 4;
constexpr int STAGE_BYTES = 40960;
constexpr int A_BYTES = 16384;
constexpr int SBUF_OFF = STAGES * STAGE_BYTES;
constexpr int EXT_OFF = SBUF_OFF + 49152;
constexpr int X_A = 0, X_Z = 2048, X_B = 4096, X_ONES = 10240, X_RSTD = 10368, X_RED = 10880, X_NRM = 14976, X_TAG = 16000;
constexpr int BAR_OFF = EXT_OFF + 16384;
constexpr int SMEM_BYTES = BAR_OFF + 128;
#define JSPLIT 6
constexpr int NCTA = 128;
constexpr float LN_EPS = 1e-5f;
static_assert(SMEM_BYTES <= 232448, "smem");

enum { M_X, M_HRE, M_HIM, M_WIN, M_SRE, M_SIM, M_WSP, M_ABT, M_Z2NT, M_HT, M_HTLD, M_WOUT, M_OUT, M_XRES, M_COUNT };
struct Maps { CUtensorMap m[M_COUNT]; };

typedef unsigned long long u64;
__device__ __align__(1024) __nv_bfloat16 g_abT[DM * 2 * SEQ];
__device__ __align__(1024) __nv_bfloat16 g_z2nT[FH * SEQ];
__device__ __align__(1024) __nv_bfloat16 g_hT[FH * SEQ];
__device__ __align__(128) u64 g_rowstat[SEQ * 2];
__device__ __align__(128) u64 g_hsum[2 * DM];
__device__ __align__(128) u64 g_wsum[2 * FH * 6];
__device__ __align__(128) u64 g_z2stat[SEQ * 8];
enum { FL_AB = 0, FL_Z2N = 128, FL_H = 192, FL_F = 256, FL_COUNT = 320 };
__device__ __align__(128) unsigned g_flags[FL_COUNT];
__device__ unsigned g_ticket;

#define TSTAMP(id)
#define TSTAMP1(id)
#define TSTAMP_G(id)

__device__ __forceinline__ uint32_t smem_u32(const void* p) { return (uint32_t)__cvta_generic_to_shared(p); }
__device__ __forceinline__ void mbar_init(uint32_t bar, uint32_t cnt) { asm volatile("mbarrier.init.shared::cta.b64 [%0], %1;" :: "r"(bar), "r"(cnt) : "memory"); }
__device__ __forceinline__ void mbar_expect_tx(uint32_t bar, uint32_t bytes) { asm volatile("mbarrier.arrive.expect_tx.shared::cta.b64 _, [%0], %1;" :: "r"(bar), "r"(bytes) : "memory"); }
__device__ __forceinline__ void mbar_arrive(uint32_t bar) { asm volatile("mbarrier.arrive.shared::cta.b64 _, [%0];" :: "r"(bar) : "memory"); }
__device__ __forceinline__ void mbar_arrive_cluster(uint32_t bar, uint32_t cta) {
  asm volatile("{\n.reg .b32 ra;\nmapa.shared::cluster.u32 ra, %0, %1;\nmbarrier.arrive.shared::cluster.b64 _, [ra];\n}\n" :: "r"(bar), "r"(cta) : "memory");
}
__device__ __forceinline__ void mbar_wait(uint32_t bar, uint32_t parity) {
  asm volatile("{\n.reg .pred p;\n.reg .u32 c;\nmov.u32 c, 0;\nLAB_WAIT:\n"
               "mbarrier.try_wait.parity.shared::cta.b64 p, [%0], %1;\n@p bra LAB_DONE;\n"
               "add.u32 c, c, 1;\nsetp.lt.u32 p, c, 200000;\n@p bra LAB_WAIT;\nLAB_DONE:\n}\n" :: "r"(bar), "r"(parity) : "memory");
}
__device__ __forceinline__ void tma_load(uint32_t dst, const CUtensorMap* tm, uint32_t bar, int c0, int c1) {
  asm volatile("cp.async.bulk.tensor.2d.shared::cluster.global.mbarrier::complete_tx::bytes [%0], [%1, {%3, %4}], [%2];"
    :: "r"(dst), "l"((uint64_t)tm), "r"(bar), "r"(c0), "r"(c1) : "memory");
}
__device__ __forceinline__ void tma_load_mc(uint32_t dst, const CUtensorMap* tm, uint32_t bar, int c0, int c1) {
  asm volatile("cp.async.bulk.tensor.2d.shared::cluster.global.mbarrier::complete_tx::bytes.multicast::cluster [%0], [%1, {%3, %4}], [%2], %5;"
    :: "r"(dst), "l"((uint64_t)tm), "r"(bar), "r"(c0), "r"(c1), "h"((uint16_t)3) : "memory");
}
__device__ __forceinline__ void tma_store(const CUtensorMap* tm, uint32_t src, int c0, int c1, int live) {
  asm volatile("{\n.reg .pred p;\nsetp.ne.b32 p, %4, 0;\n@p cp.async.bulk.tensor.2d.global.shared::cta.bulk_group [%0, {%2, %3}], [%1];\n}\n"
    :: "l"((uint64_t)tm), "r"(src), "r"(c0), "r"(c1), "r"(live) : "memory");
}
__device__ __forceinline__ void tma_reduce_add(const CUtensorMap* tm, uint32_t src, int c0, int c1, int live) {
  asm volatile("{\n.reg .pred p;\nsetp.ne.b32 p, %4, 0;\n@p cp.reduce.async.bulk.tensor.2d.global.shared::cta.add.bulk_group [%0, {%2, %3}], [%1];\n}\n"
    :: "l"((uint64_t)tm), "r"(src), "r"(c0), "r"(c1), "r"(live) : "memory");
}
__device__ __forceinline__ void bulk_commit() { asm volatile("cp.async.bulk.commit_group;" ::: "memory"); }
__device__ __forceinline__ void bulk_wait_all() { asm volatile("cp.async.bulk.wait_group 0;" ::: "memory"); }
__device__ __forceinline__ void l2_prefetch(const void* p, uint32_t bytes) {
  asm volatile("cp.async.bulk.prefetch.L2.global [%0], %1;" :: "l"((uint64_t)p), "r"(bytes) : "memory");
}
__device__ __forceinline__ void prefetch_tmap(const CUtensorMap* tm) { asm volatile("prefetch.tensormap [%0];" :: "l"((uint64_t)tm) : "memory"); }
__device__ __forceinline__ void fence_async_smem() { asm volatile("fence.proxy.async.shared::cta;" ::: "memory"); }
__device__ __forceinline__ void fence_async_global() { asm volatile("fence.proxy.async.global;" ::: "memory"); }
__device__ __forceinline__ void wgmma_fence() { asm volatile("wgmma.fence.sync.aligned;" ::: "memory"); }
__device__ __forceinline__ void wgmma_commit() { asm volatile("wgmma.commit_group.sync.aligned;" ::: "memory"); }
template<int N> __device__ __forceinline__ void wgmma_wait() { asm volatile("wgmma.wait_group.sync.aligned %0;" :: "n"(N) : "memory"); }
__device__ __forceinline__ void cluster_arrive() { asm volatile("barrier.cluster.arrive.relaxed.aligned;" ::: "memory"); }
__device__ __forceinline__ void cluster_wait() { asm volatile("barrier.cluster.wait.acquire.aligned;" ::: "memory"); }
__device__ __forceinline__ void named_sync(int id, int n) { asm volatile("bar.sync %0, %1;" :: "r"(id), "r"(n) : "memory"); }
__device__ __forceinline__ void stmatrix_x4(uint32_t addr, uint32_t r0, uint32_t r1, uint32_t r2, uint32_t r3, int live) {
  asm volatile("{\n.reg .pred p;\nsetp.ne.b32 p, %5, 0;\n@p stmatrix.sync.aligned.m8n8.x4.shared.b16 [%0], {%1, %2, %3, %4};\n}\n"
    :: "r"(addr), "r"(r0), "r"(r1), "r"(r2), "r"(r3), "r"(live) : "memory");
}
__device__ __forceinline__ void stmatrix_x4_t(uint32_t addr, uint32_t r0, uint32_t r1, uint32_t r2, uint32_t r3, int live) {
  asm volatile("{\n.reg .pred p;\nsetp.ne.b32 p, %5, 0;\n@p stmatrix.sync.aligned.m8n8.x4.trans.shared.b16 [%0], {%1, %2, %3, %4};\n}\n"
    :: "r"(addr), "r"(r0), "r"(r1), "r"(r2), "r"(r3), "r"(live) : "memory");
}
__device__ __forceinline__ void ldmatrix_x4_t(uint32_t addr, uint32_t (&r)[4]) {
  asm volatile("ldmatrix.sync.aligned.m8n8.x4.trans.shared.b16 {%0, %1, %2, %3}, [%4];" : "=r"(r[0]), "=r"(r[1]), "=r"(r[2]), "=r"(r[3]) : "r"(addr) : "memory");
}
__device__ __forceinline__ void sts128u(uint32_t addr, uint32_t a, uint32_t b, uint32_t c, uint32_t d, int live) {
  asm volatile("{\n.reg .pred p;\nsetp.ne.b32 p, %5, 0;\n@p st.shared.v4.b32 [%0], {%1, %2, %3, %4};\n}\n" :: "r"(addr), "r"(a), "r"(b), "r"(c), "r"(d), "r"(live) : "memory");
}
__device__ __forceinline__ float4 lds128(uint32_t addr) {
  float4 v; asm volatile("ld.shared.v4.f32 {%0, %1, %2, %3}, [%4];" : "=f"(v.x), "=f"(v.y), "=f"(v.z), "=f"(v.w) : "r"(addr) : "memory"); return v;
}
__device__ __forceinline__ uint4 lds128u(uint32_t addr) {
  uint4 v; asm volatile("ld.shared.v4.u32 {%0, %1, %2, %3}, [%4];" : "=r"(v.x), "=r"(v.y), "=r"(v.z), "=r"(v.w) : "r"(addr) : "memory"); return v;
}
__device__ __forceinline__ float2 lds64(uint32_t addr) {
  float2 v; asm volatile("ld.shared.v2.f32 {%0, %1}, [%2];" : "=f"(v.x), "=f"(v.y) : "r"(addr) : "memory"); return v;
}
__device__ __forceinline__ void sts64(uint32_t addr, float a, float b, int live) {
  asm volatile("{\n.reg .pred p;\nsetp.ne.b32 p, %3, 0;\n@p st.shared.v2.f32 [%0], {%1, %2};\n}\n" :: "r"(addr), "f"(a), "f"(b), "r"(live) : "memory");
}
__device__ __forceinline__ void sts32(uint32_t addr, float a) { asm volatile("st.shared.f32 [%0], %1;" :: "r"(addr), "f"(a) : "memory"); }
__device__ __forceinline__ float lds32(uint32_t addr) { float v; asm volatile("ld.shared.f32 %0, [%1];" : "=f"(v) : "r"(addr) : "memory"); return v; }
__device__ __forceinline__ uint32_t pack_bf16(float lo, float hi) {
  uint32_t r; asm("cvt.rn.bf16x2.f32 %0, %1, %2;" : "=r"(r) : "f"(hi), "f"(lo)); return r;
}
__device__ __forceinline__ uint32_t mul_bf16x2(uint32_t a, uint32_t b) {
  uint32_t r; asm("mul.rn.bf16x2 %0, %1, %2;" : "=r"(r) : "r"(a), "r"(b)); return r;
}
__device__ __forceinline__ float bf_lo(uint32_t v) { return __uint_as_float(v << 16); }
__device__ __forceinline__ float bf_hi(uint32_t v) { return __uint_as_float(v & 0xffff0000u); }
__device__ __forceinline__ float bf_round(float v) { return bf_lo(pack_bf16(v, 0.f)); }
__device__ __forceinline__ void mma16816(float (&d)[4], uint32_t a0, uint32_t a1, uint32_t a2, uint32_t a3, uint32_t b0, uint32_t b1) {
  asm volatile("mma.sync.aligned.m16n8k16.row.col.f32.bf16.bf16.f32 {%0, %1, %2, %3}, {%4, %5, %6, %7}, {%8, %9}, {%0, %1, %2, %3};"
    : "+f"(d[0]), "+f"(d[1]), "+f"(d[2]), "+f"(d[3]) : "r"(a0), "r"(a1), "r"(a2), "r"(a3), "r"(b0), "r"(b1));
}

__device__ __forceinline__ u64 tagged(float v, unsigned tag) { return ((u64)tag << 32) | __float_as_uint(v); }
__device__ __forceinline__ void st_tag1(u64* p, u64 a) { asm volatile("st.relaxed.gpu.global.b64 [%0], %1;" :: "l"(p), "l"(a) : "memory"); }
__device__ __forceinline__ void st_tag2(u64* p, u64 a, u64 b, int live) {
  asm volatile("{\n.reg .pred p;\nsetp.ne.b32 p, %3, 0;\n@p st.relaxed.gpu.global.v2.b64 [%0], {%1, %2};\n}\n" :: "l"(p), "l"(a), "l"(b), "r"(live) : "memory");
}
__device__ __forceinline__ uint2 ld_tag1(const u64* p) {
  u64 a; asm volatile("ld.relaxed.gpu.global.b64 %0, [%1];" : "=l"(a) : "l"(p) : "memory");
  return make_uint2((uint32_t)a, (uint32_t)(a >> 32));
}
__device__ __forceinline__ uint4 ld_tag2(const u64* p) {
  u64 a, b; asm volatile("ld.relaxed.gpu.global.v2.b64 {%0, %1}, [%2];" : "=l"(a), "=l"(b) : "l"(p) : "memory");
  return make_uint4((uint32_t)a, (uint32_t)(a >> 32), (uint32_t)b, (uint32_t)(b >> 32));
}
__device__ __forceinline__ void flag_set(int id, unsigned tag, int live) {
  asm volatile("{\n.reg .pred p;\nsetp.ne.b32 p, %2, 0;\n@p st.relaxed.gpu.global.u32 [%0], %1;\n}\n" :: "l"(g_flags + id), "r"(tag), "r"(live) : "memory");
}
__device__ __forceinline__ unsigned flag_get(int id) {
  unsigned v; asm volatile("ld.acquire.gpu.global.u32 %0, [%1];" : "=r"(v) : "l"(g_flags + id) : "memory"); return v;
}
constexpr int SPIN_MAX = 2000000;

__device__ __forceinline__ float gelu_half(float h) {
  const float K1 = 2.0f * 0.7978845608f, K2 = 8.0f * 0.7978845608f * 0.044715f;
  float a = h * fmaf(h * h, K2, K1);
  float t; asm("tanh.approx.f32 %0, %1;" : "=f"(t) : "f"(a));
  return fmaf(h, t, h);
}

template<int N, int TA, int TB> struct Wgmma;
template<int TA, int TB> struct Wgmma<160, TA, TB> {
  static __device__ __forceinline__ void mma(float (&d)[80], uint64_t da, uint64_t db, int scale_d) {
    asm volatile("{\n.reg .pred p;\nsetp.ne.b32 p, %82, 0;\n"
      "wgmma.mma_async.sync.aligned.m64n160k16.f32.bf16.bf16 {%0, %1, %2, %3, %4, %5, %6, %7, %8, %9, %10, %11, %12, %13, %14, %15, %16, %17, %18, %19, %20, %21, %22, %23, %24, %25, %26, %27, %28, %29, %30, %31, %32, %33, %34, %35, %36, %37, %38, %39, %40, %41, %42, %43, %44, %45, %46, %47, %48, %49, %50, %51, %52, %53, %54, %55, %56, %57, %58, %59, %60, %61, %62, %63, %64, %65, %66, %67, %68, %69, %70, %71, %72, %73, %74, %75, %76, %77, %78, %79}, %80, %81, p, 1, 1, %83, %84;\n}\n"
      : "+f"(d[0]), "+f"(d[1]), "+f"(d[2]), "+f"(d[3]), "+f"(d[4]), "+f"(d[5]), "+f"(d[6]), "+f"(d[7]), "+f"(d[8]), "+f"(d[9]), "+f"(d[10]), "+f"(d[11]), "+f"(d[12]), "+f"(d[13]), "+f"(d[14]), "+f"(d[15]), "+f"(d[16]), "+f"(d[17]), "+f"(d[18]), "+f"(d[19]), "+f"(d[20]), "+f"(d[21]), "+f"(d[22]), "+f"(d[23]), "+f"(d[24]), "+f"(d[25]), "+f"(d[26]), "+f"(d[27]), "+f"(d[28]), "+f"(d[29]), "+f"(d[30]), "+f"(d[31]), "+f"(d[32]), "+f"(d[33]), "+f"(d[34]), "+f"(d[35]), "+f"(d[36]), "+f"(d[37]), "+f"(d[38]), "+f"(d[39]), "+f"(d[40]), "+f"(d[41]), "+f"(d[42]), "+f"(d[43]), "+f"(d[44]), "+f"(d[45]), "+f"(d[46]), "+f"(d[47]), "+f"(d[48]), "+f"(d[49]), "+f"(d[50]), "+f"(d[51]), "+f"(d[52]), "+f"(d[53]), "+f"(d[54]), "+f"(d[55]), "+f"(d[56]), "+f"(d[57]), "+f"(d[58]), "+f"(d[59]), "+f"(d[60]), "+f"(d[61]), "+f"(d[62]), "+f"(d[63]), "+f"(d[64]), "+f"(d[65]), "+f"(d[66]), "+f"(d[67]), "+f"(d[68]), "+f"(d[69]), "+f"(d[70]), "+f"(d[71]), "+f"(d[72]), "+f"(d[73]), "+f"(d[74]), "+f"(d[75]), "+f"(d[76]), "+f"(d[77]), "+f"(d[78]), "+f"(d[79])
      : "l"(da), "l"(db), "r"(scale_d), "n"(TA), "n"(TB));
  }
};
template<int TA, int TB> struct Wgmma<192, TA, TB> {
  static __device__ __forceinline__ void mma(float (&d)[96], uint64_t da, uint64_t db, int scale_d) {
    asm volatile("{\n.reg .pred p;\nsetp.ne.b32 p, %98, 0;\n"
      "wgmma.mma_async.sync.aligned.m64n192k16.f32.bf16.bf16 {%0, %1, %2, %3, %4, %5, %6, %7, %8, %9, %10, %11, %12, %13, %14, %15, %16, %17, %18, %19, %20, %21, %22, %23, %24, %25, %26, %27, %28, %29, %30, %31, %32, %33, %34, %35, %36, %37, %38, %39, %40, %41, %42, %43, %44, %45, %46, %47, %48, %49, %50, %51, %52, %53, %54, %55, %56, %57, %58, %59, %60, %61, %62, %63, %64, %65, %66, %67, %68, %69, %70, %71, %72, %73, %74, %75, %76, %77, %78, %79, %80, %81, %82, %83, %84, %85, %86, %87, %88, %89, %90, %91, %92, %93, %94, %95}, %96, %97, p, 1, 1, %99, %100;\n}\n"
      : "+f"(d[0]), "+f"(d[1]), "+f"(d[2]), "+f"(d[3]), "+f"(d[4]), "+f"(d[5]), "+f"(d[6]), "+f"(d[7]), "+f"(d[8]), "+f"(d[9]), "+f"(d[10]), "+f"(d[11]), "+f"(d[12]), "+f"(d[13]), "+f"(d[14]), "+f"(d[15]), "+f"(d[16]), "+f"(d[17]), "+f"(d[18]), "+f"(d[19]), "+f"(d[20]), "+f"(d[21]), "+f"(d[22]), "+f"(d[23]), "+f"(d[24]), "+f"(d[25]), "+f"(d[26]), "+f"(d[27]), "+f"(d[28]), "+f"(d[29]), "+f"(d[30]), "+f"(d[31]), "+f"(d[32]), "+f"(d[33]), "+f"(d[34]), "+f"(d[35]), "+f"(d[36]), "+f"(d[37]), "+f"(d[38]), "+f"(d[39]), "+f"(d[40]), "+f"(d[41]), "+f"(d[42]), "+f"(d[43]), "+f"(d[44]), "+f"(d[45]), "+f"(d[46]), "+f"(d[47]), "+f"(d[48]), "+f"(d[49]), "+f"(d[50]), "+f"(d[51]), "+f"(d[52]), "+f"(d[53]), "+f"(d[54]), "+f"(d[55]), "+f"(d[56]), "+f"(d[57]), "+f"(d[58]), "+f"(d[59]), "+f"(d[60]), "+f"(d[61]), "+f"(d[62]), "+f"(d[63]), "+f"(d[64]), "+f"(d[65]), "+f"(d[66]), "+f"(d[67]), "+f"(d[68]), "+f"(d[69]), "+f"(d[70]), "+f"(d[71]), "+f"(d[72]), "+f"(d[73]), "+f"(d[74]), "+f"(d[75]), "+f"(d[76]), "+f"(d[77]), "+f"(d[78]), "+f"(d[79]), "+f"(d[80]), "+f"(d[81]), "+f"(d[82]), "+f"(d[83]), "+f"(d[84]), "+f"(d[85]), "+f"(d[86]), "+f"(d[87]), "+f"(d[88]), "+f"(d[89]), "+f"(d[90]), "+f"(d[91]), "+f"(d[92]), "+f"(d[93]), "+f"(d[94]), "+f"(d[95])
      : "l"(da), "l"(db), "r"(scale_d), "n"(TA), "n"(TB));
  }
};

__device__ __forceinline__ uint64_t make_desc(uint32_t addr, uint32_t lbo, uint32_t sbo, uint32_t swz) {
  return (uint64_t)((addr & 0x3FFFF) >> 4) | ((uint64_t)(lbo >> 4) << 16) | ((uint64_t)(sbo >> 4) << 32) | ((uint64_t)swz << 62);
}

enum { B_FULL = 0, B_EMPTY = STAGES, B_SFREE = 2 * STAGES, B_Z1RDY, B_TURN0, B_TURN1, B_TAB, B_PRE, B_XRES, B_TAG, B_COUNT };

struct Ctx {
  uint32_t base;
  int warp, lane;
  __device__ __forceinline__ uint32_t bar(int i) const { return base + BAR_OFF + 8 * i; }
  __device__ __forceinline__ uint32_t ext(int off) const { return base + EXT_OFF + off; }
  __device__ __forceinline__ unsigned tag() const { mbar_wait(bar(B_TAG), 0); return __float_as_uint(lds32(ext(X_TAG))); }
};

__device__ __forceinline__ void release_stage(const Ctx& c, int it) {
  if (c.lane < 2) mbar_arrive_cluster(c.bar(B_EMPTY + (it & (STAGES - 1))), c.lane);
}

template<int N, int TA, int TB>
__device__ __forceinline__ void mainloop(const Ctx& c, float (&acc)[2][N / 2], int it0, int n, bool pend, uint32_t pass_bar) {
  #pragma unroll 1
  for (int k = 0; k < n; k++) {
    int it = it0 + k, s = it & (STAGES - 1);
    mbar_wait(c.bar(B_FULL + s), (it / STAGES) & 1);
    if (pass_bar && k == n - 1 && c.lane == 0 && c.warp == 0) mbar_arrive(pass_bar);
    uint32_t sa = c.base + s * STAGE_BYTES;
    uint64_t da = make_desc(sa, TA == 0 ? 16 : 8192, 1024, 1);
    uint64_t db = make_desc(sa + A_BYTES, TB == 0 ? 16 : 8192, 1024, 1);
    wgmma_fence();
    #pragma unroll
    for (int kk = 0; kk < 4; kk++) {
      int sd = (!pend && k == 0 && kk == 0) ? 0 : 1;
      #pragma unroll
      for (int mb = 0; mb < 2; mb++)
        Wgmma<N, TA, TB>::mma(acc[mb], da + (uint64_t)(mb * 512 + (TA == 0 ? kk * 2 : kk * 128)), db + (uint64_t)(TB == 0 ? kk * 2 : kk * 128), sd);
    }
    wgmma_commit();
    if (k > 0 || pend) { wgmma_wait<1>(); release_stage(c, it - 1); }
  }
}
template<int N>
__device__ __forceinline__ void fence_acc(float (&acc)[2][N / 2]) {
  #pragma unroll
  for (int mb = 0; mb < 2; mb++)
    #pragma unroll
    for (int e = 0; e < N / 2; e++) asm volatile("" : "+f"(acc[mb][e]) :: "memory");
}
template<int N>
__device__ __forceinline__ void drain(const Ctx& c, float (&acc)[2][N / 2], int it_last) {
  wgmma_wait<0>();
  fence_acc<N>(acc);
  release_stage(c, it_last);
}
template<int N>
__device__ __forceinline__ void drain_ext(const Ctx& c, float (&acc)[2][N / 2], int it_last, uint32_t b_addr, uint32_t b_sbo) {
  wgmma_wait<0>();
  release_stage(c, it_last);
  mbar_wait(c.bar(B_TAB), 0);
  uint64_t da = make_desc(c.ext(X_A), 2048, 128, 0), db = make_desc(b_addr, 0, b_sbo, 0);
  wgmma_fence();
  Wgmma<N, 0, 0>::mma(acc[0], da, db, 1);
  Wgmma<N, 0, 0>::mma(acc[1], da + 64, db, 1);
  wgmma_commit();
  wgmma_wait<0>();
  fence_acc<N>(acc);
}

__device__ __forceinline__ uint32_t stage_t_addr(const Ctx& c) {
  int mi = c.lane >> 3, r = c.lane & 7;
  return c.base + SBUF_OFF + ((mi >> 1) * 8 + r) * 128 + (((2 * c.warp + (mi & 1)) ^ r) << 4);
}

__device__ __forceinline__ void split3(float v, float& a, float& b, float& d) {
  a = bf_round(v); b = bf_round(v - a); d = bf_round(v - a - b);
}

__global__ void __cluster_dims__(2, 1, 1) __launch_bounds__(384, 1)
fused_kernel(const __grid_constant__ Maps maps, const __nv_bfloat16* __restrict__ x, const __nv_bfloat16* __restrict__ hre,
             const __nv_bfloat16* __restrict__ him, const __nv_bfloat16* __restrict__ sre,
             const __nv_bfloat16* __restrict__ sim, const __nv_bfloat16* __restrict__ wsp, const __nv_bfloat16* __restrict__ bsp,
             const __nv_bfloat16* __restrict__ wout) {
  extern __shared__ __align__(1024) uint8_t smem_raw[];
  Ctx c;
  c.base = smem_u32(smem_raw);
  const int wg = __shfl_sync(0xffffffffu, threadIdx.x >> 7, 0), tid = threadIdx.x & 127;
  c.warp = __shfl_sync(0xffffffffu, tid >> 5, 0); c.lane = tid & 31;
  const int cta = blockIdx.x, rank = cta & 1, pair = cta >> 1;
  const bool isG = pair & 1;
  const int q = pair >> 1, rb = q >> 1, ct = (q & 1) * 2 + rank;
  const int row0 = rb * 128;
  const uint32_t sbuf = c.base + SBUF_OFF;

  if (threadIdx.x == 256) {
    #pragma unroll
    for (int s = 0; s < B_COUNT; s++)
      mbar_init(c.bar(s), (s >= B_EMPTY && s < B_EMPTY + STAGES) ? 8 : (s == B_Z1RDY || s == B_TAB) ? 128 : 1);
    asm volatile("fence.mbarrier_init.release.cluster;" ::: "memory");
  } else if (threadIdx.x >= 288 && threadIdx.x < 288 + M_COUNT) {
    prefetch_tmap(&maps.m[threadIdx.x - 288]);
  }
  if (threadIdx.x == 0) { TSTAMP1(0); TSTAMP_G(30); }
  __syncwarp();
  cluster_arrive();

  if (wg == 2) {
    asm volatile("setmaxnreg.dec.sync.aligned.u32 40;");
    if (c.warp == 0) {
      cluster_wait();
      if (c.lane == 0) TSTAMP1(43);
      const int nseg = isG ? 5 : 4;
      int it = 0;
      #pragma unroll 1
      for (int sg = 0; sg < nseg; sg++) {
        int ma, mb, ka = 0, kb = 0, n, nb0, fl = -1, nfl = 16; bool mn = false; uint32_t bytes = A_BYTES + 160 * 128;
        if (!isG) {
          nb0 = ct * 160;
          if (sg < 2) { ma = M_X; mb = M_HRE + sg; n = 10; }
          else { ma = M_SRE + sg - 2; mb = M_ABT; kb = (sg - 2) * SEQ; n = sg == 2 ? 32 : 32 - JSPLIT; fl = FL_AB + ((sg - 2) * 4 + ct) * 16; }
        } else if (sg == 3) {
          ma = M_SIM; mb = M_ABT; n = JSPLIT; ka = (32 - JSPLIT) * 64; kb = SEQ + ka; nb0 = ct * 160; fl = FL_AB + (4 + ct) * 16;
        } else {
          bytes = A_BYTES + 192 * 128;
          if (sg < 2) { ma = M_X; mb = M_WIN; n = 10; nb0 = (sg ? 0 : FH) + ct * 192; mn = true; }
          else if (sg == 2) { ma = M_WSP; mb = M_Z2NT; n = 32; nb0 = ct * 192; fl = FL_Z2N + ct * 16; }
          else { ma = M_HTLD; mb = M_WOUT; n = 12; nb0 = ct * 160; mn = true; fl = FL_H + rb * 4; nfl = 4; }
        }
        const bool a_dep = sg == 4;
        #pragma unroll 1
        for (int k = 0; k < n; k++, it++) {
          const int s = it & (STAGES - 1);
          const uint32_t sa = c.base + s * STAGE_BYTES, fb = c.bar(B_FULL + s);
          #pragma unroll 1
          for (int ph = 0; ph < 2; ph++) {
            if (c.lane == 0) {
              if (ph == 0) { mbar_wait(c.bar(B_EMPTY + s), ((it / STAGES) & 1) ^ 1); mbar_expect_tx(fb, bytes); }
              if ((ph == 1) == a_dep) {
                tma_load_mc(sa + rank * 8192, &maps.m[ma], fb, a_dep ? row0 + rank * 64 : ka + k * 64, a_dep ? k * 64 : row0 + rank * 64);
              } else if (!mn) {
                tma_load(sa + A_BYTES, &maps.m[mb], fb, kb + k * 64, nb0);
              } else {
                #pragma unroll 1
                for (int b = 0; b < 3; b++) tma_load(sa + A_BYTES + b * 8192, &maps.m[mb], fb, nb0 + b * 64, k * 64);
              }
            }
            if (ph == 0 && k == 0 && fl >= 0) {
              __syncwarp();
              if (c.lane == 0) TSTAMP1(18 + sg * 2);
              const unsigned tag = c.tag();
              #pragma unroll 1
              for (int sp = 0; sp < SPIN_MAX; sp++) {
                bool ok = c.lane >= nfl || flag_get(fl + c.lane) == tag;
                if (__all_sync(0xffffffffu, ok)) break;
              }
              fence_async_global();
              if (c.lane == 0) TSTAMP1(19 + sg * 2);
            }
          }
        }
      }
    } else {
      const int ht = tid - 32;
      const bool do_w = cta < 120;
      const int wcb = cta % 24, wrr = cta / 24;
      unsigned tk = 0;
      if (ht == 32) tk = atomicAdd(&g_ticket, 1u);
      cluster_wait();
      if (ht == 0 && do_w) {
        mbar_expect_tx(c.bar(B_PRE), 16384);
        tma_load(sbuf, &maps.m[M_WIN], c.bar(B_PRE), wcb * 64, wrr * 128);
        tma_load(sbuf + 8192, &maps.m[M_WIN], c.bar(B_PRE), wcb * 64, wrr * 128 + 64);
      }
      if (ht == 32) { sts32(c.ext(X_TAG), __uint_as_float((tk >> 7) + 1u)); mbar_arrive(c.bar(B_TAG)); }
      if (do_w) {
        mbar_wait(c.bar(B_PRE), 0);
        if (ht == 0) TSTAMP1(33);
        float w[8];
        #pragma unroll
        for (int e = 0; e < 8; e++) w[e] = 0.f;
        #pragma unroll 1
        for (int r = ht >> 3; r < 128; r += 24) {
          const int r2 = r + 12;
          uint4 v = lds128u(sbuf + r * 128 + (((ht & 7) ^ (r & 7)) << 4));
          uint4 u = lds128u(sbuf + (r2 & 127) * 128 + (((ht & 7) ^ (r2 & 7)) << 4));
          if (r2 >= 128) u = make_uint4(0, 0, 0, 0);
          w[0] += bf_lo(v.x) + bf_lo(u.x); w[1] += bf_hi(v.x) + bf_hi(u.x); w[2] += bf_lo(v.y) + bf_lo(u.y); w[3] += bf_hi(v.y) + bf_hi(u.y);
          w[4] += bf_lo(v.z) + bf_lo(u.z); w[5] += bf_hi(v.z) + bf_hi(u.z); w[6] += bf_lo(v.w) + bf_lo(u.w); w[7] += bf_hi(v.w) + bf_hi(u.w);
        }
        __syncwarp();
        #pragma unroll
        for (int e = 0; e < 8; e++) { w[e] += __shfl_xor_sync(0xffffffffu, w[e], 8); w[e] += __shfl_xor_sync(0xffffffffu, w[e], 16); }
        const uint32_t red = sbuf + 16384;
        const uint32_t ra = red + (c.warp - 1) * 256 + (c.lane & 7) * 32;
        sts128u(ra, __float_as_uint(w[0]), __float_as_uint(w[1]), __float_as_uint(w[2]), __float_as_uint(w[3]), c.lane < 8);
        sts128u(ra + 16, __float_as_uint(w[4]), __float_as_uint(w[5]), __float_as_uint(w[6]), __float_as_uint(w[7]), c.lane < 8);
        named_sync(3, 96);
        const unsigned tag = c.tag();
        if (ht < 64) st_tag1(&g_wsum[(wcb * 64 + ht) * 6 + wrr], tagged(lds32(red + ht * 4) + lds32(red + 256 + ht * 4) + lds32(red + 512 + ht * 4), tag));
        if (ht == 0) TSTAMP1(35);
      }
      {
        const __nv_bfloat16* pm = isG ? wsp : sre;
        const size_t off = (size_t)(row0 + ct * 32 + c.lane) * SEQ;
        #pragma unroll 1
        for (int sgm = c.warp - 1; sgm < 8; sgm += 3) l2_prefetch(pm + off + sgm * 256, 512);
        if (isG) { if (ht < 12) l2_prefetch(wout + (size_t)((rb * 4 + ct) * 12 + ht) * DM, DM * 2); }
        else {
          __nanosleep(2000);
          #pragma unroll 1
          for (int sgm = c.warp - 1; sgm < 8; sgm += 3) l2_prefetch(sim + off + sgm * 256, 512);
        }
        if (ht == 0) TSTAMP1(38);
      }
    }
  } else {
    asm volatile("setmaxnreg.inc.sync.aligned.u32 232;");
    const uint32_t a0 = stage_t_addr(c);
    const int barid = 1 + wg;
    if (wg == 1) {
      const int nq = c.lane >> 2;
      const bool isx = c.warp < 2;
      const __nv_bfloat16* src = isx ? x + (size_t)cta * 16 * DM : (cta < 64 ? hre : him) + (size_t)(cta & 63) * 10 * DM;
      const uint4* p0 = (const uint4*)(src + nq * DM + (c.warp & 1) * 320) + (c.lane & 3);
      const uint4* p1 = (const uint4*)(src + (isx ? nq + 8 : min(nq + 8, 9)) * DM + (c.warp & 1) * 320) + (c.lane & 3);
      uint4 r0[10], r1[10];
      #pragma unroll
      for (int i = 0; i < 10; i++) { r0[i] = __ldg(p0 + 4 * i); r1[i] = __ldg(p1 + 4 * i); }
      cluster_wait();
      float d1[4] = {0.f, 0.f, 0.f, 0.f}, d2[4] = {0.f, 0.f, 0.f, 0.f}, d3[4] = {0.f, 0.f, 0.f, 0.f};
      #pragma unroll
      for (int i = 0; i < 10; i++) {
        mma16816(d1, r0[i].x, r1[i].x, r0[i].y, r1[i].y, 0x3F803F80u, 0x3F803F80u);
        mma16816(d2, r0[i].x, r1[i].x, r0[i].y, r1[i].y, r0[i].x, r0[i].y);
        mma16816(d3, r0[i].x, r1[i].x, r0[i].y, r1[i].y, r1[i].x, r1[i].y);
        mma16816(d1, r0[i].z, r1[i].z, r0[i].w, r1[i].w, 0x3F803F80u, 0x3F803F80u);
        mma16816(d2, r0[i].z, r1[i].z, r0[i].w, r1[i].w, r0[i].z, r0[i].w);
        mma16816(d3, r0[i].z, r1[i].z, r0[i].w, r1[i].w, r1[i].z, r1[i].w);
      }
      const bool own = (c.lane & 3) == (nq >> 1);
      const uint32_t ra = c.ext(X_RED) + c.warp * 128 + nq * 16;
      sts128u(ra, __float_as_uint(d1[0]), __float_as_uint((nq & 1) ? d2[1] : d2[0]), __float_as_uint(d1[2]), __float_as_uint((nq & 1) ? d3[3] : d3[2]), own);
      named_sync(barid, 128);
      const unsigned tag = c.tag();
      if (tid < 32) {
        const int row = tid & 15;
        const uint32_t sa = c.ext(X_RED) + (tid >> 4) * 256 + (row & 7) * 16 + (row >> 3) * 8;
        float2 u = lds64(sa), v = lds64(sa + 128);
        float s = u.x + v.x, sq = u.y + v.y;
        if (tid < 16) {
          float mean = s * (1.0f / DM);
          st_tag2(&g_rowstat[(cta * 16 + row) * 2], tagged(mean, tag), tagged(rsqrtf(fmaxf(sq * (1.0f / DM) - mean * mean, 0.f) + LN_EPS), tag), 1);
        } else if (row < 10) st_tag1(&g_hsum[cta * 10 + row], tagged(s, tag));
      }
      TSTAMP(2);
    } else {
      cluster_wait();
    }

    auto build_tables = [&]() {
      TSTAMP(36);
      const unsigned tag = c.tag();
      const int NT = isG ? 192 : 160;
      uint4 rs; float cs[3];
      #pragma unroll 1
      for (int sp = 0; sp < SPIN_MAX; sp++) {
        rs = ld_tag2(&g_rowstat[(row0 + tid) * 2]);
        bool ok = rs.y == tag && rs.w == tag;
        #pragma unroll
        for (int i = 0; i < 3; i++) {
          const int ii = min(tid + i * 128, 2 * NT - 1), t = ii >= NT, n = ii - t * NT;
          if (isG) {
            const u64* p = &g_wsum[((t ? 0 : FH) + ct * 192 + n) * 6];
            uint4 e0 = ld_tag2(p), e1 = ld_tag2(p + 2); uint2 e2 = ld_tag1(p + 4);
            ok = ok && e0.y == tag && e0.w == tag && e1.y == tag && e1.w == tag && e2.y == tag;
            cs[i] = ((__uint_as_float(e0.x) + __uint_as_float(e0.z)) + (__uint_as_float(e1.x) + __uint_as_float(e1.z))) + __uint_as_float(e2.x);
          } else {
            uint2 e = ld_tag1(&g_hsum[t * DM + ct * 160 + n]);
            ok = ok && e.y == tag;
            cs[i] = __uint_as_float(e.x);
          }
        }
        if (ok) break;
      }
      float m1, m2, m3;
      split3(-__uint_as_float(rs.x), m1, m2, m3);
      sts128u(c.ext(X_A) + tid * 16, pack_bf16(m1, m1), pack_bf16(m2, m1), pack_bf16(m2, m3), pack_bf16(__bfloat162float(bsp[row0 + tid]), 0.f), 1);
      sts128u(c.ext(X_Z) + tid * 16, 0, 0, 0, 0, 1);
      sts32(c.ext(X_RSTD) + tid * 4, __uint_as_float(rs.z));
      #pragma unroll
      for (int i = 0; i < 3; i++) {
        const int ii = min(tid + i * 128, 2 * NT - 1), t = ii >= NT, n = ii - t * NT;
        split3(cs[i], m1, m2, m3);
        sts128u(c.ext(X_B) + t * 3072 + n * 16, pack_bf16(m1, m2), pack_bf16(m1, m3), pack_bf16(m2, m1), 0, 1);
      }
      sts128u(c.ext(X_ONES) + (tid & 7) * 16, 0, 0, 0, 0x00003F80u, tid < 8);
      fence_async_smem();
      mbar_arrive(c.bar(B_TAB));
      TSTAMP(3);
    };

    float acc[2][80];
    if (!isG) {
      #pragma unroll 1
      for (int live = wg ^ 1; live < 2; live++) {
        if (live) {
          if (wg == 1) mbar_wait(c.bar(B_TURN1), 0);
          mainloop<160, 0, 0>(c, acc, wg * 10, 10, false, c.bar(B_TURN0 + (wg ^ 1)));
          drain_ext<160>(c, acc, wg * 10 + 9, c.ext(X_B) + wg * 3072, 128);
          TSTAMP(4 + wg * 4);
          if (wg == 1) mbar_wait(c.bar(B_SFREE), 0);
        }
        #pragma unroll
        for (int mb = 0; mb < 2; mb++) {
          const uint32_t ra = c.ext(X_RSTD) + (mb * 64 + c.warp * 16 + (c.lane >> 2)) * 4;
          float s0 = lds32(ra), s1 = lds32(ra + 32);
          if (wg == 1) { s0 = -s0; s1 = -s1; }
          #pragma unroll
          for (int j = 0; j < 20; j += 2)
            stmatrix_x4_t(a0 + mb * (160 * 128) + j * 1024,
                          pack_bf16(acc[mb][4 * j + 0] * s0, acc[mb][4 * j + 1] * s0), pack_bf16(acc[mb][4 * j + 2] * s1, acc[mb][4 * j + 3] * s1),
                          pack_bf16(acc[mb][4 * j + 4] * s0, acc[mb][4 * j + 5] * s0), pack_bf16(acc[mb][4 * j + 6] * s1, acc[mb][4 * j + 7] * s1), live);
        }
        fence_async_smem();
        named_sync(barid, 128);
        if (tid == 0) {
          if (live) TSTAMP1(6 + wg * 4);
          tma_store(&maps.m[M_ABT], sbuf, wg * SEQ + row0, ct * 160, live);
          tma_store(&maps.m[M_ABT], sbuf + 160 * 128, wg * SEQ + row0 + 64, ct * 160, live);
          bulk_commit();
          const unsigned tag = c.tag();
          bulk_wait_all();
          flag_set(FL_AB + (wg * 4 + ct) * 16 + rb, tag, live);
          if (live) TSTAMP1(7 + wg * 4);
          if (live && wg == 0) mbar_arrive(c.bar(B_SFREE));
        }
        if (!live) build_tables();
      }
      if (wg == 1) {
        if (tid == 0) {
          mbar_expect_tx(c.bar(B_XRES), 128 * 160 * 2);
          #pragma unroll 1
          for (int b = 0; b < 5; b++) tma_load(sbuf + b * 8192, &maps.m[M_XRES], c.bar(B_XRES), ct * 160 + b * 32, row0);
          mbar_wait(c.bar(B_XRES), 0);
          #pragma unroll 1
          for (int b = 0; b < 5; b++) tma_store(&maps.m[M_OUT], sbuf + b * 8192, ct * 160 + b * 32, row0, 1);
          bulk_commit();
          bulk_wait_all();
          mbar_arrive(c.bar(B_SFREE));
        }
      } else {
        mbar_wait(c.bar(B_TURN0), 0);
        TSTAMP(12);
        mainloop<160, 0, 0>(c, acc, 20, 64 - JSPLIT, false, 0);
        drain<160>(c, acc, 20 + 64 - JSPLIT - 1);
        TSTAMP(13);
        mbar_wait(c.bar(B_SFREE), 1);
      }
    } else {
      float acz[2][96];
      const uint32_t e0 = sbuf + (tid >> 3) * 128 + (((tid & 7) ^ ((tid >> 3) & 7)) << 4);
      #pragma unroll 1
      for (int live = wg ^ 1; live < 2; live++) {
        if (live) {
          if (wg == 1) mbar_wait(c.bar(B_TURN1), 0);
          mainloop<192, 0, 1>(c, acz, wg * 10, 10, false, c.bar(B_TURN0 + (wg ^ 1)));
          drain_ext<192>(c, acz, wg * 10 + 9, c.ext(X_B) + wg * 3072, 128);
          TSTAMP(4 + wg * 4);
          if (wg == 1) mbar_wait(c.bar(B_SFREE), 0);
        }
        #pragma unroll
        for (int mb = 0; mb < 2; mb++)
          #pragma unroll
          for (int j = 0; j < 24; j += 2)
            stmatrix_x4_t(a0 + mb * (192 * 128) + j * 1024,
                          pack_bf16(acz[mb][4 * j + 0], acz[mb][4 * j + 1]), pack_bf16(acz[mb][4 * j + 2], acz[mb][4 * j + 3]),
                          pack_bf16(acz[mb][4 * j + 4], acz[mb][4 * j + 5]), pack_bf16(acz[mb][4 * j + 6], acz[mb][4 * j + 7]), live);
        named_sync(barid, 128);
        if (live) TSTAMP(5 + wg * 4);
        const int z2live = live && wg == 0;
        const unsigned tag = c.tag();
        #pragma unroll 1
        for (int mb = 0; mb < (live ? 2 : 1); mb++) {
          float hr[8], sm[8], sq[8];
          {
            float4 u = lds128(c.ext(X_RSTD) + mb * 256 + (tid & 7) * 32), v = lds128(c.ext(X_RSTD) + mb * 256 + (tid & 7) * 32 + 16);
            hr[0] = 0.5f * u.x; hr[1] = 0.5f * u.y; hr[2] = 0.5f * u.z; hr[3] = 0.5f * u.w;
            hr[4] = 0.5f * v.x; hr[5] = 0.5f * v.y; hr[6] = 0.5f * v.z; hr[7] = 0.5f * v.w;
          }
          #pragma unroll
          for (int e = 0; e < 8; e++) sm[e] = sq[e] = 0.f;
          #pragma unroll 1
          for (int i = 0; i < (live ? 12 : 3); i += 3) {
            uint4 v[3];
            #pragma unroll
            for (int u = 0; u < 3; u++) v[u] = lds128u(e0 + mb * (192 * 128) + (i + u) * 2048);
            #pragma unroll
            for (int u = 0; u < 3; u++) {
              uint32_t w[4] = {v[u].x, v[u].y, v[u].z, v[u].w};
              #pragma unroll
              for (int e = 0; e < 4; e++) {
                float g0 = gelu_half(bf_lo(w[e]) * hr[2 * e]), g1 = gelu_half(bf_hi(w[e]) * hr[2 * e + 1]);
                sm[2 * e] += g0; sq[2 * e] = fmaf(g0, g0, sq[2 * e]);
                sm[2 * e + 1] += g1; sq[2 * e + 1] = fmaf(g1, g1, sq[2 * e + 1]);
                w[e] = pack_bf16(g0, g1);
              }
              sts128u(e0 + mb * (192 * 128) + (i + u) * 2048, w[0], w[1], w[2], w[3], live);
            }
          }
          if (wg == 0 || !live) {
            const bool up = c.lane & 8, up2 = c.lane & 16;
            float a4[4], b4[4], a2[2], b2[2];
            #pragma unroll
            for (int e = 0; e < 4; e++) {
              a4[e] = (up ? sm[4 + e] : sm[e]) + __shfl_xor_sync(0xffffffffu, up ? sm[e] : sm[4 + e], 8);
              b4[e] = (up ? sq[4 + e] : sq[e]) + __shfl_xor_sync(0xffffffffu, up ? sq[e] : sq[4 + e], 8);
            }
            #pragma unroll
            for (int e = 0; e < 2; e++) {
              a2[e] = (up2 ? a4[2 + e] : a4[e]) + __shfl_xor_sync(0xffffffffu, up2 ? a4[e] : a4[2 + e], 16);
              b2[e] = (up2 ? b4[2 + e] : b4[e]) + __shfl_xor_sync(0xffffffffu, up2 ? b4[e] : b4[2 + e], 16);
            }
            const int srow = (c.lane & 7) * 8 + (up ? 4 : 0) + (up2 ? 2 : 0);
            sts128u(c.ext(X_RED) + mb * 2048 + c.warp * 512 + srow * 8, __float_as_uint(a2[0]), __float_as_uint(b2[0]), __float_as_uint(a2[1]), __float_as_uint(b2[1]), z2live);
            named_sync(barid, 128);
            const uint32_t ra = c.ext(X_RED) + mb * 2048 + (tid & 63) * 8;
            float2 p0 = lds64(ra), p1 = lds64(ra + 512), p2 = lds64(ra + 1024), p3 = lds64(ra + 1536);
            st_tag2(&g_z2stat[(row0 + mb * 64 + (tid & 63)) * 8 + ct * 2], tagged((p0.x + p1.x) + (p2.x + p3.x), tag),
                    tagged((p0.y + p1.y) + (p2.y + p3.y), tag), z2live && tid < 64);
          }
        }
        if (wg == 0 || !live) {
          if (live) TSTAMP(16);
          float s = 0.f, sq = 0.f;
          #pragma unroll 1
          for (int sp = 0; sp < SPIN_MAX; sp++) {
            const u64* p = &g_z2stat[(row0 + tid) * 8];
            uint4 e0_ = ld_tag2(p), e1 = ld_tag2(p + 2), e2 = ld_tag2(p + 4), e3 = ld_tag2(p + 6);
            bool ok = e0_.y == tag && e0_.w == tag && e1.y == tag && e1.w == tag && e2.y == tag && e2.w == tag && e3.y == tag && e3.w == tag;
            s = (__uint_as_float(e0_.x) + __uint_as_float(e1.x)) + (__uint_as_float(e2.x) + __uint_as_float(e3.x));
            sq = (__uint_as_float(e0_.z) + __uint_as_float(e1.z)) + (__uint_as_float(e2.z) + __uint_as_float(e3.z));
            if (ok || !live) break;
          }
          const float mean = s * (1.0f / FH), rstd = rsqrtf(fmaxf(sq * (1.0f / FH) - mean * mean, 0.f) + LN_EPS);
          sts64(c.ext(X_NRM) + tid * 8, rstd, -mean * rstd, live);
          named_sync(barid, 128);
          if (live) TSTAMP(17);
          #pragma unroll 1
          for (int mb = 0; mb < (live ? 2 : 1); mb++) {
            float4 nr[4];
            #pragma unroll
            for (int e = 0; e < 4; e++) nr[e] = lds128(c.ext(X_NRM) + mb * 512 + (tid & 7) * 64 + e * 16);
            #pragma unroll 1
            for (int i = 0; i < (live ? 12 : 4); i += 4) {
              uint4 v[4];
              #pragma unroll
              for (int u = 0; u < 4; u++) v[u] = lds128u(e0 + mb * (192 * 128) + (i + u) * 2048);
              #pragma unroll
              for (int u = 0; u < 4; u++) {
                uint32_t w[4] = {v[u].x, v[u].y, v[u].z, v[u].w};
                #pragma unroll
                for (int e = 0; e < 4; e++) w[e] = pack_bf16(fmaf(bf_lo(w[e]), nr[e].x, nr[e].y), fmaf(bf_hi(w[e]), nr[e].z, nr[e].w));
                sts128u(e0 + mb * (192 * 128) + (i + u) * 2048, w[0], w[1], w[2], w[3], live);
              }
            }
            fence_async_smem();
            named_sync(barid, 128);
            if (tid == 0) { tma_store(&maps.m[M_Z2NT], sbuf + mb * (192 * 128), row0 + mb * 64, ct * 192, live); bulk_commit(); }
          }
          if (tid == 0) {
            if (live) TSTAMP1(6);
            bulk_wait_all();
            flag_set(FL_Z2N + ct * 16 + rb, tag, live);
            if (live) { mbar_arrive(c.bar(B_SFREE)); TSTAMP1(7); }
          }
        }
        if (!live) build_tables();
      }
      if (wg == 1) {
        mbar_arrive(c.bar(B_Z1RDY));
        TSTAMP(11);
      } else {
        mbar_wait(c.bar(B_TURN0), 0);
        TSTAMP(12);
        mainloop<192, 0, 0>(c, acz, 20, 32, false, c.bar(B_TURN1));
        drain_ext<192>(c, acz, 51, c.ext(X_ONES), 0);
        TSTAMP(13);
        mbar_wait(c.bar(B_Z1RDY), 0);
      }
      {
        const int live = wg == 0;
        #pragma unroll
        for (int mb = 0; mb < 2; mb++)
          #pragma unroll
          for (int j = 0; j < 24; j += 2) {
            const uint32_t ad = a0 + mb * (192 * 128) + j * 1024;
            uint32_t z[4];
            ldmatrix_x4_t(ad, z);
            stmatrix_x4_t(ad, mul_bf16x2(z[0], pack_bf16(acz[mb][4 * j + 0], acz[mb][4 * j + 1])), mul_bf16x2(z[1], pack_bf16(acz[mb][4 * j + 2], acz[mb][4 * j + 3])),
                              mul_bf16x2(z[2], pack_bf16(acz[mb][4 * j + 4], acz[mb][4 * j + 5])), mul_bf16x2(z[3], pack_bf16(acz[mb][4 * j + 6], acz[mb][4 * j + 7])), live);
          }
        fence_async_smem();
        named_sync(barid, 128);
        if (tid == 0) {
          if (live) TSTAMP1(37);
          tma_store(&maps.m[M_HT], sbuf, row0, ct * 192, live);
          tma_store(&maps.m[M_HT], sbuf + 192 * 128, row0 + 64, ct * 192, live);
          bulk_commit();
          const unsigned tag = c.tag();
          bulk_wait_all();
          flag_set(FL_H + rb * 4 + ct, tag, live);
          if (live) { mbar_arrive(c.bar(B_SFREE)); TSTAMP1(14); }
        }
      }
      if (wg == 1) {
        mbar_wait(c.bar(B_TURN1), 1);
        mainloop<160, 0, 0>(c, acc, 52, JSPLIT, false, 0);
        TSTAMP(15);
        mainloop<160, 1, 1>(c, acc, 52 + JSPLIT, 12, true, 0);
        drain<160>(c, acc, 52 + JSPLIT + 11);
        TSTAMP(9);
        mbar_wait(c.bar(B_SFREE), 1);
      }
    }
    {
      const int live = wg == (isG ? 1 : 0);
      const int mi = c.lane >> 3, rl = c.warp * 16 + (mi & 1) * 8 + (c.lane & 7);
      const uint32_t o0 = sbuf + rl * 64 + (((mi >> 1) ^ ((rl >> 1) & 3)) << 4);
      #pragma unroll
      for (int mb = 0; mb < 2; mb++)
        #pragma unroll
        for (int j = 0; j < 20; j += 2)
          stmatrix_x4((o0 ^ ((j & 2) << 4)) + (j >> 2) * 8192 + mb * 4096,
                      pack_bf16(acc[mb][4 * j + 0], acc[mb][4 * j + 1]), pack_bf16(acc[mb][4 * j + 2], acc[mb][4 * j + 3]),
                      pack_bf16(acc[mb][4 * j + 4], acc[mb][4 * j + 5]), pack_bf16(acc[mb][4 * j + 6], acc[mb][4 * j + 7]), live);
      fence_async_smem();
      named_sync(barid, 128);
      if (tid == 0) {
        if (live) TSTAMP1(28);
        const unsigned tag = c.tag();
        if (isG && live) {
          #pragma unroll 1
          for (int sp = 0; sp < SPIN_MAX; sp++) if (flag_get(FL_F + rb * 4 + ct) == tag) break;
          fence_async_global();
        }
        if (live) TSTAMP1(29);
        #pragma unroll 1
        for (int b = 0; b < 5; b++) tma_reduce_add(&maps.m[M_OUT], sbuf + b * 8192, ct * 160 + b * 32, row0, live);
        bulk_commit();
        bulk_wait_all();
        flag_set(FL_F + rb * 4 + ct, tag, live && !isG);
        if (live) TSTAMP1(10);
      }
    }
  }
  __syncwarp();
  cluster_arrive();
  cluster_wait();
  if (threadIdx.x == 0) { TSTAMP1(21); TSTAMP_G(31); }
}

typedef CUresult (*EncodeFn)(CUtensorMap*, CUtensorMapDataType, cuuint32_t, void*, const cuuint64_t*, const cuuint64_t*,
                             const cuuint32_t*, const cuuint32_t*, CUtensorMapInterleave, CUtensorMapSwizzle,
                             CUtensorMapL2promotion, CUtensorMapFloatOOBfill);

void make_map(EncodeFn enc, CUtensorMap* m, const void* p, int rows, int cols, int box_rows, int box_cols, CUtensorMapSwizzle sw) {
  cuuint64_t gd[2] = {(cuuint64_t)cols, (cuuint64_t)rows};
  cuuint64_t gs[1] = {(cuuint64_t)cols * 2};
  cuuint32_t bd[2] = {(cuuint32_t)box_cols, (cuuint32_t)box_rows};
  cuuint32_t es[2] = {1, 1};
  enc(m, CU_TENSOR_MAP_DATA_TYPE_BFLOAT16, 2, (void*)p, gd, gs, bd, es, CU_TENSOR_MAP_INTERLEAVE_NONE, sw,
      CU_TENSOR_MAP_L2_PROMOTION_L2_256B, CU_TENSOR_MAP_FLOAT_OOB_FILL_NONE);
}

}

extern "C" void kernel_launch(void* const* d_in, const int* in_sizes, int n_in, void* d_out, int out_size) {
  const __nv_bfloat16* x = (const __nv_bfloat16*)d_in[0];
  const __nv_bfloat16* sre = (const __nv_bfloat16*)d_in[1];
  const __nv_bfloat16* sim = (const __nv_bfloat16*)d_in[2];
  const __nv_bfloat16* hre = (const __nv_bfloat16*)d_in[3];
  const __nv_bfloat16* him = (const __nv_bfloat16*)d_in[4];
  const __nv_bfloat16* win = (const __nv_bfloat16*)d_in[6];
  const __nv_bfloat16* wsp = (const __nv_bfloat16*)d_in[7];
  const __nv_bfloat16* bsp = (const __nv_bfloat16*)d_in[8];
  const __nv_bfloat16* wout = (const __nv_bfloat16*)d_in[9];

  void* fn = nullptr;
  cudaDriverEntryPointQueryResult qr;
  cudaGetDriverEntryPoint("cuTensorMapEncodeTiled", &fn, cudaEnableDefault, &qr);
  EncodeFn enc = (EncodeFn)fn;
  void *p_abT, *p_z2nT, *p_hT;
  cudaGetSymbolAddress(&p_abT, g_abT);
  cudaGetSymbolAddress(&p_z2nT, g_z2nT);
  cudaGetSymbolAddress(&p_hT, g_hT);
  Maps m;
  const CUtensorMapSwizzle S128 = CU_TENSOR_MAP_SWIZZLE_128B, S64 = CU_TENSOR_MAP_SWIZZLE_64B;
  make_map(enc, &m.m[M_X], x, SEQ, DM, 64, 64, S128);
  make_map(enc, &m.m[M_HRE], hre, DM, DM, 160, 64, S128);
  make_map(enc, &m.m[M_HIM], him, DM, DM, 160, 64, S128);
  make_map(enc, &m.m[M_WIN], win, DM, 2 * FH, 64, 64, S128);
  make_map(enc, &m.m[M_SRE], sre, SEQ, SEQ, 64, 64, S128);
  make_map(enc, &m.m[M_SIM], sim, SEQ, SEQ, 64, 64, S128);
  make_map(enc, &m.m[M_WSP], wsp, SEQ, SEQ, 64, 64, S128);
  make_map(enc, &m.m[M_ABT], p_abT, DM, 2 * SEQ, 160, 64, S128);
  make_map(enc, &m.m[M_Z2NT], p_z2nT, FH, SEQ, 192, 64, S128);
  make_map(enc, &m.m[M_HT], p_hT, FH, SEQ, 192, 64, S128);
  make_map(enc, &m.m[M_HTLD], p_hT, FH, SEQ, 64, 64, S128);
  make_map(enc, &m.m[M_WOUT], wout, FH, DM, 64, 64, S128);
  make_map(enc, &m.m[M_OUT], d_out, SEQ, DM, 128, 32, S64);
  make_map(enc, &m.m[M_XRES], x, SEQ, DM, 128, 32, S64);
  cudaFuncSetAttribute(fused_kernel, cudaFuncAttributeMaxDynamicSharedMemorySize, SMEM_BYTES);
  fused_kernel<<<NCTA, 384, SMEM_BYTES>>>(m, x, hre, him, sre, sim, wsp, bsp, wout);
}
```

```cpp
#include <cuda.h>
#include <cuda_runtime.h>
#include <cuda_bf16.h>
#include <stdint.h>

extern __shared__ __align__(1024) uint8_t smem_raw[];

namespace {

constexpr int SEQ = 2048, DM = 640, FH = 768;
constexpr int STAGES = 4;
constexpr int STAGE_BYTES = 40960;
constexpr int A_BYTES = 16384;
constexpr int SBUF_OFF = STAGES * STAGE_BYTES;
constexpr int EXT_OFF = SBUF_OFF + 49152;
constexpr int X_A = 0, X_Z = 2048, X_B = 4096, X_ONES = 10240, X_RSTD = 10368, X_RED = 10880, X_NRM = 14976, X_TAG = 16000, X_ZERO = 16128;
constexpr int BAR_OFF = EXT_OFF + 16384;
constexpr int SMEM_BYTES = BAR_OFF + 256;
#define JSPLIT 6
constexpr int NCTA = 128;
constexpr float LN_EPS = 1e-5f;
static_assert(SMEM_BYTES <= 232448, "smem");

enum { M_X, M_HRE, M_HIM, M_WIN, M_SRE, M_SIM, M_WSP, M_ABT, M_Z2NT, M_HT, M_HTLD, M_WOUT, M_OUT, M_XRES, M_WCOL, M_COUNT };
struct Maps { CUtensorMap m[M_COUNT]; };

typedef unsigned long long u64;
__device__ __align__(1024) __nv_bfloat16 g_abT[DM * 2 * SEQ];
__device__ __align__(1024) __nv_bfloat16 g_z2nT[FH * SEQ];
__device__ __align__(1024) __nv_bfloat16 g_hT[FH * SEQ];
__device__ __align__(128) u64 g_rowstat[SEQ * 2];
__device__ __align__(128) u64 g_csum[2 * DM + 2 * FH];
__device__ __align__(128) u64 g_z2stat[SEQ * 8];
enum { FL_AB = 0, FL_Z2N = 128, FL_H = 256, FL_F = 320, FL_COUNT = 384 };
__device__ __align__(128) unsigned g_flags[FL_COUNT];
__device__ unsigned g_ticket;

#define TSTAMP(id)
#define TSTAMP1(id)
#define TSTAMP_G(id)

__device__ __forceinline__ uint32_t smem_u32(const void* p) { return (uint32_t)__cvta_generic_to_shared(p); }
__device__ __forceinline__ void mbar_init(uint32_t bar, uint32_t cnt) { asm volatile("mbarrier.init.shared::cta.b64 [%0], %1;" :: "r"(bar), "r"(cnt) : "memory"); }
__device__ __forceinline__ void mbar_expect_tx(uint32_t bar, uint32_t bytes) { asm volatile("mbarrier.arrive.expect_tx.shared::cta.b64 _, [%0], %1;" :: "r"(bar), "r"(bytes) : "memory"); }
__device__ __forceinline__ void mbar_arrive(uint32_t bar) { asm volatile("mbarrier.arrive.shared::cta.b64 _, [%0];" :: "r"(bar) : "memory"); }
__device__ __forceinline__ void mbar_arrive_if(uint32_t bar, int live) {
  asm volatile("{\n.reg .pred p;\nsetp.ne.b32 p, %1, 0;\n@p mbarrier.arrive.shared::cta.b64 _, [%0];\n}\n" :: "r"(bar), "r"(live) : "memory");
}
__device__ __forceinline__ void mbar_arrive_cluster(uint32_t bar, uint32_t cta) {
  asm volatile("{\n.reg .b32 ra;\nmapa.shared::cluster.u32 ra, %0, %1;\nmbarrier.arrive.shared::cluster.b64 _, [ra];\n}\n" :: "r"(bar), "r"(cta) : "memory");
}
__device__ __forceinline__ void mbar_wait(uint32_t bar, uint32_t parity) {
  asm volatile("{\n.reg .pred p;\n.reg .u32 c;\nmov.u32 c, 0;\nLAB_WAIT:\n"
               "mbarrier.try_wait.parity.shared::cta.b64 p, [%0], %1;\n@p bra LAB_DONE;\n"
               "add.u32 c, c, 1;\nsetp.lt.u32 p, c, 200000;\n@p bra LAB_WAIT;\nLAB_DONE:\n}\n" :: "r"(bar), "r"(parity) : "memory");
}
__device__ __forceinline__ void tma_load(uint32_t dst, const CUtensorMap* tm, uint32_t bar, int c0, int c1) {
  asm volatile("cp.async.bulk.tensor.2d.shared::cluster.global.mbarrier::complete_tx::bytes [%0], [%1, {%3, %4}], [%2];"
    :: "r"(dst), "l"((uint64_t)tm), "r"(bar), "r"(c0), "r"(c1) : "memory");
}
__device__ __forceinline__ void tma_load_mc(uint32_t dst, const CUtensorMap* tm, uint32_t bar, int c0, int c1) {
  asm volatile("cp.async.bulk.tensor.2d.shared::cluster.global.mbarrier::complete_tx::bytes.multicast::cluster [%0], [%1, {%3, %4}], [%2], %5;"
    :: "r"(dst), "l"((uint64_t)tm), "r"(bar), "r"(c0), "r"(c1), "h"((uint16_t)3) : "memory");
}
__device__ __forceinline__ void bulk_load(uint32_t dst, const void* src, uint32_t bytes, uint32_t bar) {
  asm volatile("cp.async.bulk.shared::cluster.global.mbarrier::complete_tx::bytes [%0], [%1], %2, [%3];"
    :: "r"(dst), "l"((uint64_t)src), "r"(bytes), "r"(bar) : "memory");
}
__device__ __forceinline__ void tma_store(const CUtensorMap* tm, uint32_t src, int c0, int c1, int live) {
  asm volatile("{\n.reg .pred p;\nsetp.ne.b32 p, %4, 0;\n@p cp.async.bulk.tensor.2d.global.shared::cta.bulk_group [%0, {%2, %3}], [%1];\n}\n"
    :: "l"((uint64_t)tm), "r"(src), "r"(c0), "r"(c1), "r"(live) : "memory");
}
__device__ __forceinline__ void tma_reduce_add(const CUtensorMap* tm, uint32_t src, int c0, int c1, int live) {
  asm volatile("{\n.reg .pred p;\nsetp.ne.b32 p, %4, 0;\n@p cp.reduce.async.bulk.tensor.2d.global.shared::cta.add.bulk_group [%0, {%2, %3}], [%1];\n}\n"
    :: "l"((uint64_t)tm), "r"(src), "r"(c0), "r"(c1), "r"(live) : "memory");
}
__device__ __forceinline__ void bulk_commit() { asm volatile("cp.async.bulk.commit_group;" ::: "memory"); }
__device__ __forceinline__ void bulk_wait_read() { asm volatile("cp.async.bulk.wait_group.read 0;" ::: "memory"); }
__device__ __forceinline__ void bulk_wait_all() { asm volatile("cp.async.bulk.wait_group 0;" ::: "memory"); }
__device__ __forceinline__ void l2_prefetch(const void* p, uint32_t bytes) {
  asm volatile("cp.async.bulk.prefetch.L2.global [%0], %1;" :: "l"((uint64_t)p), "r"(bytes) : "memory");
}
__device__ __forceinline__ void prefetch_tmap(const CUtensorMap* tm) { asm volatile("prefetch.tensormap [%0];" :: "l"((uint64_t)tm) : "memory"); }
__device__ __forceinline__ void fence_async_smem() { asm volatile("fence.proxy.async.shared::cta;" ::: "memory"); }
__device__ __forceinline__ void fence_async_global() { asm volatile("fence.proxy.async.global;" ::: "memory"); }
__device__ __forceinline__ void wgmma_fence() { asm volatile("wgmma.fence.sync.aligned;" ::: "memory"); }
__device__ __forceinline__ void wgmma_commit() { asm volatile("wgmma.commit_group.sync.aligned;" ::: "memory"); }
template<int N> __device__ __forceinline__ void wgmma_wait() { asm volatile("wgmma.wait_group.sync.aligned %0;" :: "n"(N) : "memory"); }
__device__ __forceinline__ void cluster_arrive() { asm volatile("barrier.cluster.arrive.relaxed.aligned;" ::: "memory"); }
__device__ __forceinline__ void cluster_wait() { asm volatile("barrier.cluster.wait.acquire.aligned;" ::: "memory"); }
__device__ __forceinline__ bool elect_one() {
  uint32_t p; asm volatile("{\n.reg .pred p;\nelect.sync _|p, 0xffffffff;\nselp.u32 %0, 1, 0, p;\n}\n" : "=r"(p)); return p;
}
__device__ __forceinline__ void named_sync(int id, int n) { asm volatile("bar.sync %0, %1;" :: "r"(id), "r"(n) : "memory"); }
__device__ __forceinline__ void stmatrix_x4(uint32_t addr, uint32_t r0, uint32_t r1, uint32_t r2, uint32_t r3, int live) {
  asm volatile("{\n.reg .pred p;\nsetp.ne.b32 p, %5, 0;\n@p stmatrix.sync.aligned.m8n8.x4.shared.b16 [%0], {%1, %2, %3, %4};\n}\n"
    :: "r"(addr), "r"(r0), "r"(r1), "r"(r2), "r"(r3), "r"(live) : "memory");
}
__device__ __forceinline__ void stmatrix_x4_t(uint32_t addr, uint32_t r0, uint32_t r1, uint32_t r2, uint32_t r3, int live) {
  asm volatile("{\n.reg .pred p;\nsetp.ne.b32 p, %5, 0;\n@p stmatrix.sync.aligned.m8n8.x4.trans.shared.b16 [%0], {%1, %2, %3, %4};\n}\n"
    :: "r"(addr), "r"(r0), "r"(r1), "r"(r2), "r"(r3), "r"(live) : "memory");
}
__device__ __forceinline__ void ldmatrix_x4_t(uint32_t addr, uint32_t (&r)[4]) {
  asm volatile("ldmatrix.sync.aligned.m8n8.x4.trans.shared.b16 {%0, %1, %2, %3}, [%4];" : "=r"(r[0]), "=r"(r[1]), "=r"(r[2]), "=r"(r[3]) : "r"(addr) : "memory");
}
__device__ __forceinline__ void sts128u(uint32_t addr, uint32_t a, uint32_t b, uint32_t c, uint32_t d, int live) {
  asm volatile("{\n.reg .pred p;\nsetp.ne.b32 p, %5, 0;\n@p st.shared.v4.b32 [%0], {%1, %2, %3, %4};\n}\n" :: "r"(addr), "r"(a), "r"(b), "r"(c), "r"(d), "r"(live) : "memory");
}
__device__ __forceinline__ float4 lds128(uint32_t addr) {
  float4 v; asm volatile("ld.shared.v4.f32 {%0, %1, %2, %3}, [%4];" : "=f"(v.x), "=f"(v.y), "=f"(v.z), "=f"(v.w) : "r"(addr) : "memory"); return v;
}
__device__ __forceinline__ uint4 lds128u(uint32_t addr) {
  uint4 v; asm volatile("ld.shared.v4.u32 {%0, %1, %2, %3}, [%4];" : "=r"(v.x), "=r"(v.y), "=r"(v.z), "=r"(v.w) : "r"(addr) : "memory"); return v;
}
__device__ __forceinline__ float2 lds64(uint32_t addr) {
  float2 v; asm volatile("ld.shared.v2.f32 {%0, %1}, [%2];" : "=f"(v.x), "=f"(v.y) : "r"(addr) : "memory"); return v;
}
__device__ __forceinline__ void sts64(uint32_t addr, float a, float b, int live) {
  asm volatile("{\n.reg .pred p;\nsetp.ne.b32 p, %3, 0;\n@p st.shared.v2.f32 [%0], {%1, %2};\n}\n" :: "r"(addr), "f"(a), "f"(b), "r"(live) : "memory");
}
__device__ __forceinline__ void sts32(uint32_t addr, float a) { asm volatile("st.shared.f32 [%0], %1;" :: "r"(addr), "f"(a) : "memory"); }
__device__ __forceinline__ float lds32(uint32_t addr) { float v; asm volatile("ld.shared.f32 %0, [%1];" : "=f"(v) : "r"(addr) : "memory"); return v; }
__device__ __forceinline__ uint32_t pack_bf16(float lo, float hi) {
  uint32_t r; asm("cvt.rn.bf16x2.f32 %0, %1, %2;" : "=r"(r) : "f"(hi), "f"(lo)); return r;
}
__device__ __forceinline__ uint32_t mul_bf16x2(uint32_t a, uint32_t b) {
  uint32_t r; asm("mul.rn.bf16x2 %0, %1, %2;" : "=r"(r) : "r"(a), "r"(b)); return r;
}
__device__ __forceinline__ float bf_lo(uint32_t v) { return __uint_as_float(v << 16); }
__device__ __forceinline__ float bf_hi(uint32_t v) { return __uint_as_float(v & 0xffff0000u); }
__device__ __forceinline__ float bf_round(float v) { return bf_lo(pack_bf16(v, 0.f)); }

__device__ __forceinline__ u64 tagged(float v, unsigned tag) { return ((u64)tag << 32) | __float_as_uint(v); }
__device__ __forceinline__ void st_tag1(u64* p, u64 a) { asm volatile("st.relaxed.gpu.global.b64 [%0], %1;" :: "l"(p), "l"(a) : "memory"); }
__device__ __forceinline__ void st_tag2(u64* p, u64 a, u64 b, int live) {
  asm volatile("{\n.reg .pred p;\nsetp.ne.b32 p, %3, 0;\n@p st.relaxed.gpu.global.v2.b64 [%0], {%1, %2};\n}\n" :: "l"(p), "l"(a), "l"(b), "r"(live) : "memory");
}
__device__ __forceinline__ uint2 ld_tag1(const u64* p) {
  u64 a; asm volatile("ld.relaxed.gpu.global.b64 %0, [%1];" : "=l"(a) : "l"(p) : "memory");
  return make_uint2((uint32_t)a, (uint32_t)(a >> 32));
}
__device__ __forceinline__ uint4 ld_tag2(const u64* p) {
  u64 a, b; asm volatile("ld.relaxed.gpu.global.v2.b64 {%0, %1}, [%2];" : "=l"(a), "=l"(b) : "l"(p) : "memory");
  return make_uint4((uint32_t)a, (uint32_t)(a >> 32), (uint32_t)b, (uint32_t)(b >> 32));
}
__device__ __forceinline__ void flag_set(int id, unsigned tag, int live) {
  asm volatile("{\n.reg .pred p;\nsetp.ne.b32 p, %2, 0;\n@p st.relaxed.gpu.global.u32 [%0], %1;\n}\n" :: "l"(g_flags + id), "r"(tag), "r"(live) : "memory");
}
__device__ __forceinline__ unsigned flag_get(int id) {
  unsigned v; asm volatile("ld.acquire.gpu.global.u32 %0, [%1];" : "=r"(v) : "l"(g_flags + id) : "memory"); return v;
}
constexpr int SPIN_MAX = 2000000;
#define POLL_NS 100

__device__ __forceinline__ float gelu_half(float h) {
  const float K1 = 2.0f * 0.7978845608f, K2 = 8.0f * 0.7978845608f * 0.044715f;
  float a = h * fmaf(h * h, K2, K1);
  float t; asm("tanh.approx.f32 %0, %1;" : "=f"(t) : "f"(a));
  return fmaf(h, t, h);
}

template<int N, int TA, int TB> struct Wgmma;
template<int TA, int TB> struct Wgmma<160, TA, TB> {
  static __device__ __forceinline__ void mma(float (&d)[80], uint64_t da, uint64_t db, int scale_d) {
    asm volatile("{\n.reg .pred p;\nsetp.ne.b32 p, %82, 0;\n"
      "wgmma.mma_async.sync.aligned.m64n160k16.f32.bf16.bf16 {%0, %1, %2, %3, %4, %5, %6, %7, %8, %9, %10, %11, %12, %13, %14, %15, %16, %17, %18, %19, %20, %21, %22, %23, %24, %25, %26, %27, %28, %29, %30, %31, %32, %33, %34, %35, %36, %37, %38, %39, %40, %41, %42, %43, %44, %45, %46, %47, %48, %49, %50, %51, %52, %53, %54, %55, %56, %57, %58, %59, %60, %61, %62, %63, %64, %65, %66, %67, %68, %69, %70, %71, %72, %73, %74, %75, %76, %77, %78, %79}, %80, %81, p, 1, 1, %83, %84;\n}\n"
      : "+f"(d[0]), "+f"(d[1]), "+f"(d[2]), "+f"(d[3]), "+f"(d[4]), "+f"(d[5]), "+f"(d[6]), "+f"(d[7]), "+f"(d[8]), "+f"(d[9]), "+f"(d[10]), "+f"(d[11]), "+f"(d[12]), "+f"(d[13]), "+f"(d[14]), "+f"(d[15]), "+f"(d[16]), "+f"(d[17]), "+f"(d[18]), "+f"(d[19]), "+f"(d[20]), "+f"(d[21]), "+f"(d[22]), "+f"(d[23]), "+f"(d[24]), "+f"(d[25]), "+f"(d[26]), "+f"(d[27]), "+f"(d[28]), "+f"(d[29]), "+f"(d[30]), "+f"(d[31]), "+f"(d[32]), "+f"(d[33]), "+f"(d[34]), "+f"(d[35]), "+f"(d[36]), "+f"(d[37]), "+f"(d[38]), "+f"(d[39]), "+f"(d[40]), "+f"(d[41]), "+f"(d[42]), "+f"(d[43]), "+f"(d[44]), "+f"(d[45]), "+f"(d[46]), "+f"(d[47]), "+f"(d[48]), "+f"(d[49]), "+f"(d[50]), "+f"(d[51]), "+f"(d[52]), "+f"(d[53]), "+f"(d[54]), "+f"(d[55]), "+f"(d[56]), "+f"(d[57]), "+f"(d[58]), "+f"(d[59]), "+f"(d[60]), "+f"(d[61]), "+f"(d[62]), "+f"(d[63]), "+f"(d[64]), "+f"(d[65]), "+f"(d[66]), "+f"(d[67]), "+f"(d[68]), "+f"(d[69]), "+f"(d[70]), "+f"(d[71]), "+f"(d[72]), "+f"(d[73]), "+f"(d[74]), "+f"(d[75]), "+f"(d[76]), "+f"(d[77]), "+f"(d[78]), "+f"(d[79])
      : "l"(da), "l"(db), "r"(scale_d), "n"(TA), "n"(TB));
  }
  static __device__ __forceinline__ void mma_first(float (&d)[80], uint64_t da, uint64_t db) {
    asm volatile("{\n.reg .pred p;\nsetp.ne.b32 p, 0, 0;\n"
      "wgmma.mma_async.sync.aligned.m64n160k16.f32.bf16.bf16 {%0, %1, %2, %3, %4, %5, %6, %7, %8, %9, %10, %11, %12, %13, %14, %15, %16, %17, %18, %19, %20, %21, %22, %23, %24, %25, %26, %27, %28, %29, %30, %31, %32, %33, %34, %35, %36, %37, %38, %39, %40, %41, %42, %43, %44, %45, %46, %47, %48, %49, %50, %51, %52, %53, %54, %55, %56, %57, %58, %59, %60, %61, %62, %63, %64, %65, %66, %67, %68, %69, %70, %71, %72, %73, %74, %75, %76, %77, %78, %79}, %80, %81, p, 1, 1, %82, %83;\n}\n"
      : "=f"(d[0]), "=f"(d[1]), "=f"(d[2]), "=f"(d[3]), "=f"(d[4]), "=f"(d[5]), "=f"(d[6]), "=f"(d[7]), "=f"(d[8]), "=f"(d[9]), "=f"(d[10]), "=f"(d[11]), "=f"(d[12]), "=f"(d[13]), "=f"(d[14]), "=f"(d[15]), "=f"(d[16]), "=f"(d[17]), "=f"(d[18]), "=f"(d[19]), "=f"(d[20]), "=f"(d[21]), "=f"(d[22]), "=f"(d[23]), "=f"(d[24]), "=f"(d[25]), "=f"(d[26]), "=f"(d[27]), "=f"(d[28]), "=f"(d[29]), "=f"(d[30]), "=f"(d[31]), "=f"(d[32]), "=f"(d[33]), "=f"(d[34]), "=f"(d[35]), "=f"(d[36]), "=f"(d[37]), "=f"(d[38]), "=f"(d[39]), "=f"(d[40]), "=f"(d[41]), "=f"(d[42]), "=f"(d[43]), "=f"(d[44]), "=f"(d[45]), "=f"(d[46]), "=f"(d[47]), "=f"(d[48]), "=f"(d[49]), "=f"(d[50]), "=f"(d[51]), "=f"(d[52]), "=f"(d[53]), "=f"(d[54]), "=f"(d[55]), "=f"(d[56]), "=f"(d[57]), "=f"(d[58]), "=f"(d[59]), "=f"(d[60]), "=f"(d[61]), "=f"(d[62]), "=f"(d[63]), "=f"(d[64]), "=f"(d[65]), "=f"(d[66]), "=f"(d[67]), "=f"(d[68]), "=f"(d[69]), "=f"(d[70]), "=f"(d[71]), "=f"(d[72]), "=f"(d[73]), "=f"(d[74]), "=f"(d[75]), "=f"(d[76]), "=f"(d[77]), "=f"(d[78]), "=f"(d[79])
      : "l"(da), "l"(db), "n"(TA), "n"(TB));
  }
};
template<int TA, int TB> struct Wgmma<192, TA, TB> {
  static __device__ __forceinline__ void mma(float (&d)[96], uint64_t da, uint64_t db, int scale_d) {
    asm volatile("{\n.reg .pred p;\nsetp.ne.b32 p, %98, 0;\n"
      "wgmma.mma_async.sync.aligned.m64n192k16.f32.bf16.bf16 {%0, %1, %2, %3, %4, %5, %6, %7, %8, %9, %10, %11, %12, %13, %14, %15, %16, %17, %18, %19, %20, %21, %22, %23, %24, %25, %26, %27, %28, %29, %30, %31, %32, %33, %34, %35, %36, %37, %38, %39, %40, %41, %42, %43, %44, %45, %46, %47, %48, %49, %50, %51, %52, %53, %54, %55, %56, %57, %58, %59, %60, %61, %62, %63, %64, %65, %66, %67, %68, %69, %70, %71, %72, %73, %74, %75, %76, %77, %78, %79, %80, %81, %82, %83, %84, %85, %86, %87, %88, %89, %90, %91, %92, %93, %94, %95}, %96, %97, p, 1, 1, %99, %100;\n}\n"
      : "+f"(d[0]), "+f"(d[1]), "+f"(d[2]), "+f"(d[3]), "+f"(d[4]), "+f"(d[5]), "+f"(d[6]), "+f"(d[7]), "+f"(d[8]), "+f"(d[9]), "+f"(d[10]), "+f"(d[11]), "+f"(d[12]), "+f"(d[13]), "+f"(d[14]), "+f"(d[15]), "+f"(d[16]), "+f"(d[17]), "+f"(d[18]), "+f"(d[19]), "+f"(d[20]), "+f"(d[21]), "+f"(d[22]), "+f"(d[23]), "+f"(d[24]), "+f"(d[25]), "+f"(d[26]), "+f"(d[27]), "+f"(d[28]), "+f"(d[29]), "+f"(d[30]), "+f"(d[31]), "+f"(d[32]), "+f"(d[33]), "+f"(d[34]), "+f"(d[35]), "+f"(d[36]), "+f"(d[37]), "+f"(d[38]), "+f"(d[39]), "+f"(d[40]), "+f"(d[41]), "+f"(d[42]), "+f"(d[43]), "+f"(d[44]), "+f"(d[45]), "+f"(d[46]), "+f"(d[47]), "+f"(d[48]), "+f"(d[49]), "+f"(d[50]), "+f"(d[51]), "+f"(d[52]), "+f"(d[53]), "+f"(d[54]), "+f"(d[55]), "+f"(d[56]), "+f"(d[57]), "+f"(d[58]), "+f"(d[59]), "+f"(d[60]), "+f"(d[61]), "+f"(d[62]), "+f"(d[63]), "+f"(d[64]), "+f"(d[65]), "+f"(d[66]), "+f"(d[67]), "+f"(d[68]), "+f"(d[69]), "+f"(d[70]), "+f"(d[71]), "+f"(d[72]), "+f"(d[73]), "+f"(d[74]), "+f"(d[75]), "+f"(d[76]), "+f"(d[77]), "+f"(d[78]), "+f"(d[79]), "+f"(d[80]), "+f"(d[81]), "+f"(d[82]), "+f"(d[83]), "+f"(d[84]), "+f"(d[85]), "+f"(d[86]), "+f"(d[87]), "+f"(d[88]), "+f"(d[89]), "+f"(d[90]), "+f"(d[91]), "+f"(d[92]), "+f"(d[93]), "+f"(d[94]), "+f"(d[95])
      : "l"(da), "l"(db), "r"(scale_d), "n"(TA), "n"(TB));
  }
  static __device__ __forceinline__ void mma_first(float (&d)[96], uint64_t da, uint64_t db) {
    asm volatile("{\n.reg .pred p;\nsetp.ne.b32 p, 0, 0;\n"
      "wgmma.mma_async.sync.aligned.m64n192k16.f32.bf16.bf16 {%0, %1, %2, %3, %4, %5, %6, %7, %8, %9, %10, %11, %12, %13, %14, %15, %16, %17, %18, %19, %20, %21, %22, %23, %24, %25, %26, %27, %28, %29, %30, %31, %32, %33, %34, %35, %36, %37, %38, %39, %40, %41, %42, %43, %44, %45, %46, %47, %48, %49, %50, %51, %52, %53, %54, %55, %56, %57, %58, %59, %60, %61, %62, %63, %64, %65, %66, %67, %68, %69, %70, %71, %72, %73, %74, %75, %76, %77, %78, %79, %80, %81, %82, %83, %84, %85, %86, %87, %88, %89, %90, %91, %92, %93, %94, %95}, %96, %97, p, 1, 1, %98, %99;\n}\n"
      : "=f"(d[0]), "=f"(d[1]), "=f"(d[2]), "=f"(d[3]), "=f"(d[4]), "=f"(d[5]), "=f"(d[6]), "=f"(d[7]), "=f"(d[8]), "=f"(d[9]), "=f"(d[10]), "=f"(d[11]), "=f"(d[12]), "=f"(d[13]), "=f"(d[14]), "=f"(d[15]), "=f"(d[16]), "=f"(d[17]), "=f"(d[18]), "=f"(d[19]), "=f"(d[20]), "=f"(d[21]), "=f"(d[22]), "=f"(d[23]), "=f"(d[24]), "=f"(d[25]), "=f"(d[26]), "=f"(d[27]), "=f"(d[28]), "=f"(d[29]), "=f"(d[30]), "=f"(d[31]), "=f"(d[32]), "=f"(d[33]), "=f"(d[34]), "=f"(d[35]), "=f"(d[36]), "=f"(d[37]), "=f"(d[38]), "=f"(d[39]), "=f"(d[40]), "=f"(d[41]), "=f"(d[42]), "=f"(d[43]), "=f"(d[44]), "=f"(d[45]), "=f"(d[46]), "=f"(d[47]), "=f"(d[48]), "=f"(d[49]), "=f"(d[50]), "=f"(d[51]), "=f"(d[52]), "=f"(d[53]), "=f"(d[54]), "=f"(d[55]), "=f"(d[56]), "=f"(d[57]), "=f"(d[58]), "=f"(d[59]), "=f"(d[60]), "=f"(d[61]), "=f"(d[62]), "=f"(d[63]), "=f"(d[64]), "=f"(d[65]), "=f"(d[66]), "=f"(d[67]), "=f"(d[68]), "=f"(d[69]), "=f"(d[70]), "=f"(d[71]), "=f"(d[72]), "=f"(d[73]), "=f"(d[74]), "=f"(d[75]), "=f"(d[76]), "=f"(d[77]), "=f"(d[78]), "=f"(d[79]), "=f"(d[80]), "=f"(d[81]), "=f"(d[82]), "=f"(d[83]), "=f"(d[84]), "=f"(d[85]), "=f"(d[86]), "=f"(d[87]), "=f"(d[88]), "=f"(d[89]), "=f"(d[90]), "=f"(d[91]), "=f"(d[92]), "=f"(d[93]), "=f"(d[94]), "=f"(d[95])
      : "l"(da), "l"(db), "n"(TA), "n"(TB));
  }
};

__device__ __forceinline__ uint64_t make_desc(uint32_t addr, uint32_t lbo, uint32_t sbo, uint32_t swz) {
  return (uint64_t)((addr & 0x3FFFF) >> 4) | ((uint64_t)(lbo >> 4) << 16) | ((uint64_t)(sbo >> 4) << 32) | ((uint64_t)swz << 62);
}

enum { B_FULL = 0, B_EMPTY = STAGES, B_SFREE = 2 * STAGES, B_Z1RDY, B_TURN0, B_TURN1, B_TAB, B_PRE, B_XRES, B_TAG, B_ROWS, B_STORE, B_COUNT };

template<int V> struct IC { static constexpr int value = V; };
struct Ctx {
  uint32_t base;
  int warp, lane;
  __device__ __forceinline__ uint32_t bar(int i) const { return base + BAR_OFF + 8 * i; }
  __device__ __forceinline__ uint32_t ext(int off) const { return base + EXT_OFF + off; }
  __device__ __forceinline__ unsigned tag() const { mbar_wait(bar(B_TAG), 0); return __float_as_uint(lds32(ext(X_TAG))); }
};

__device__ __forceinline__ void release_stage(const Ctx& c, int it) {
  if (c.lane < 2) mbar_arrive_cluster(c.bar(B_EMPTY + (it & (STAGES - 1))), c.lane);
}

template<int N, int TA, int TB, bool ZI>
__device__ __forceinline__ void mainloop(const Ctx& c, float (&acc)[2][N / 2], int it0, int n, bool pend, uint32_t pass_bar) {
  wgmma_fence();
  #pragma unroll 1
  for (int k = 0; k < n; k++) {
    int it = it0 + k, s = it & (STAGES - 1);
    mbar_wait(c.bar(B_FULL + s), (it / STAGES) & 1);
    if (pass_bar && k == n - 1 && c.lane == 0 && c.warp == 0) mbar_arrive(pass_bar);
    uint32_t sa = c.base + s * STAGE_BYTES;
    uint64_t da = make_desc(sa, TA == 0 ? 16 : 8192, 1024, 1);
    uint64_t db = make_desc(sa + A_BYTES, TB == 0 ? 16 : 8192, 1024, 1);
    wgmma_fence();
    #pragma unroll
    for (int kk = 0; kk < 4; kk++) {
      int sd = (ZI && k == 0 && kk == 0) ? 0 : 1;
      #pragma unroll
      for (int mb = 0; mb < 2; mb++)
        Wgmma<N, TA, TB>::mma(acc[mb], da + (uint64_t)(mb * 512 + (TA == 0 ? kk * 2 : kk * 128)), db + (uint64_t)(TB == 0 ? kk * 2 : kk * 128), sd);
    }
    wgmma_commit();
    if (k > 0 || pend) { wgmma_wait<1>(); release_stage(c, it - 1); }
  }
}
template<int N>
__device__ __forceinline__ void fence_acc(float (&acc)[2][N / 2]) {
  #pragma unroll
  for (int mb = 0; mb < 2; mb++)
    #pragma unroll
    for (int e = 0; e < N / 2; e++) asm volatile("" : "+f"(acc[mb][e]) :: "memory");
}
template<int N>
__device__ __forceinline__ void undef_acc(float (&acc)[2][N / 2]) {
  #pragma unroll
  for (int mb = 0; mb < 2; mb++)
    #pragma unroll
    for (int e = 0; e < N / 2; e++) asm volatile("" : "=f"(acc[mb][e]));
}
template<int N>
__device__ __forceinline__ void drain(const Ctx& c, float (&acc)[2][N / 2], int it_last) {
  wgmma_wait<0>();
  fence_acc<N>(acc);
  release_stage(c, it_last);
}
template<int N>
__device__ __forceinline__ void drain_ext(const Ctx& c, float (&acc)[2][N / 2], int it_last, uint32_t b_addr, uint32_t b_sbo) {
  wgmma_wait<0>();
  release_stage(c, it_last);
  mbar_wait(c.bar(B_TAB), 0);
  uint64_t da = make_desc(c.ext(X_A), 2048, 128, 0), db = make_desc(b_addr, 0, b_sbo, 0);
  wgmma_fence();
  Wgmma<N, 0, 0>::mma(acc[0], da, db, 1);
  Wgmma<N, 0, 0>::mma(acc[1], da + 64, db, 1);
  wgmma_commit();
  wgmma_wait<0>();
  fence_acc<N>(acc);
}

template<int N>
__device__ __forceinline__ void first_ext(const Ctx& c, float (&acc)[2][N / 2], uint32_t b_addr, uint32_t b_sbo) {
  uint64_t da = make_desc(c.ext(X_A), 2048, 128, 0), db = make_desc(b_addr, 0, b_sbo, 0);
  wgmma_fence();
  Wgmma<N, 0, 0>::mma_first(acc[0], da, db);
  Wgmma<N, 0, 0>::mma_first(acc[1], da + 64, db);
  wgmma_commit();
}

__device__ __forceinline__ uint32_t stage_t_addr(const Ctx& c) {
  int mi = c.lane >> 3, r = c.lane & 7;
  return c.base + SBUF_OFF + ((mi >> 1) * 8 + r) * 128 + (((2 * c.warp + (mi & 1)) ^ r) << 4);
}

__device__ __forceinline__ void split3(float v, float& a, float& b, float& d) {
  a = bf_round(v); b = bf_round(v - a); d = bf_round(v - a - b);
}

__global__ void __cluster_dims__(2, 1, 1) __launch_bounds__(384, 1)
fused_kernel(const __grid_constant__ Maps maps, const __nv_bfloat16* __restrict__ x, const __nv_bfloat16* __restrict__ hre,
             const __nv_bfloat16* __restrict__ him, const __nv_bfloat16* __restrict__ sre,
             const __nv_bfloat16* __restrict__ sim, const __nv_bfloat16* __restrict__ wsp, const __nv_bfloat16* __restrict__ bsp,
             const __nv_bfloat16* __restrict__ wout) {
  Ctx c;
  asm("mov.u32 %0, smem_raw;" : "=r"(c.base));
  if (threadIdx.x == 1023) smem_raw[0] = 0;
  const int wg = __shfl_sync(0xffffffffu, threadIdx.x >> 7, 0), tid = threadIdx.x & 127;
  c.warp = __shfl_sync(0xffffffffu, tid >> 5, 0); c.lane = tid & 31;
  const int cta = blockIdx.x, rank = cta & 1, pair = cta >> 1;
  const bool isG = pair & 1;
  const int q = pair >> 1, rb = q >> 1, ct = (q & 1) * 2 + rank;
  const int row0 = rb * 128;
  const uint32_t sbuf = c.base + SBUF_OFF;

  if (threadIdx.x == 256) {
    #pragma unroll
    for (int s = 0; s < B_COUNT; s++)
      mbar_init(c.bar(s), (s >= B_EMPTY && s < B_EMPTY + STAGES) ? 8 : (s == B_Z1RDY || s == B_TAB || s == B_STORE) ? 128 : 1);
    asm volatile("fence.mbarrier_init.release.cluster;" ::: "memory");
  } else if (threadIdx.x >= 288 && threadIdx.x < 288 + M_COUNT) {
    prefetch_tmap(&maps.m[threadIdx.x - 288]);
  }
  if (threadIdx.x == 0) { TSTAMP1(0); TSTAMP_G(30); }
  __syncwarp();
  cluster_arrive();

  if (wg == 2) {
    asm volatile("setmaxnreg.dec.sync.aligned.u32 40;");
    if (c.warp == 0) {
      cluster_wait();
      if (c.lane == 0) TSTAMP1(43);
      int it = 0;
      auto run = [&](auto mode_c, const CUtensorMap* ma, const CUtensorMap* mb, int ka, int kb, int ks, int n, int nb0, uint32_t bytes, int fl, int nfl, int ts) {
        constexpr int MODE = decltype(mode_c)::value;
        #pragma unroll 1
        for (int k = 0; k < n; k++, it++) {
          const int s = it & (STAGES - 1);
          const uint32_t sa = c.base + s * STAGE_BYTES, fb = c.bar(B_FULL + s);
          mbar_wait(c.bar(B_EMPTY + s), ((it / STAGES) & 1) ^ 1);
          if (elect_one()) {
            mbar_expect_tx(fb, bytes);
            if (MODE < 2) tma_load_mc(sa + rank * 8192, ma, fb, ka + k * ks, row0 + rank * 64);
            if (MODE > 0) {
              #pragma unroll
              for (int b = 0; b < 3; b++) tma_load(sa + A_BYTES + b * 8192, mb, fb, nb0 + b * 64, k * 64);
            }
          }
          if (MODE != 1) {
            if (k == 0 && fl >= 0) {
              if (c.lane == 0) TSTAMP1(ts);
              const unsigned tag = c.tag();
              #pragma unroll 1
              for (int sp = 0; sp < SPIN_MAX; sp++) {
                bool ok = flag_get(fl + (c.lane & (nfl - 1))) == tag;
                if (__all_sync(0xffffffffu, ok)) break;
                __nanosleep(POLL_NS);
              }
              fence_async_global();
              if (c.lane == 0) TSTAMP1(ts + 1);
            }
            if (elect_one()) {
              if (MODE == 0) tma_load(sa + A_BYTES, mb, fb, kb + k * ks, nb0);
              else tma_load_mc(sa + rank * 8192, ma, fb, row0 + rank * 64, k * 64);
            }
          }
        }
      };
      constexpr uint32_t B160 = A_BYTES + 160 * 128, B192 = A_BYTES + 192 * 128;
      if (isG) {
        #pragma unroll 1
        for (int t = 0; t < 2; t++) run(IC<1>(), &maps.m[M_X], &maps.m[M_WIN], 0, 0, 64, 10, (t ? 0 : FH) + ct * 192, B192, -1, 1, 0);
      }
      #pragma unroll 1
      for (int sg = 0; sg < (isG ? 3 : 4); sg++) {
        const CUtensorMap *ma, *mb; int ka = 0, kb = 0, ks = 64, n, nb0 = ct * 160, fl = -1; uint32_t bytes = B160;
        if (!isG) {
          if (sg < 2) { ma = &maps.m[M_X]; mb = &maps.m[M_HRE + sg]; n = 10; }
          else { ma = &maps.m[M_SRE + sg - 2]; mb = &maps.m[M_ABT]; kb = (sg - 2) * SEQ; n = sg == 2 ? 32 : 32 - JSPLIT; fl = FL_AB + ((sg - 2) * 4 + ct) * 16; }
        } else if (sg < 2) {
          ma = &maps.m[M_WSP]; mb = &maps.m[M_Z2NT]; n = 16; ka = kb = sg * 64; ks = 128; nb0 = ct * 192; fl = FL_Z2N + (ct * 2 + sg) * 16; bytes = B192;
        } else {
          ma = &maps.m[M_SIM]; mb = &maps.m[M_ABT]; n = JSPLIT; ka = (32 - JSPLIT) * 64; kb = SEQ + ka; fl = FL_AB + (4 + ct) * 16;
        }
        run(IC<0>(), ma, mb, ka, kb, ks, n, nb0, bytes, fl, 16, isG ? 22 + sg * 2 + (sg == 2 ? 20 : 0) : 18 + sg * 2);
      }
      if (isG) run(IC<2>(), &maps.m[M_HTLD], &maps.m[M_WOUT], 0, 0, 64, 12, ct * 160, B192, FL_H + rb * 4, 4, 26);
    } else {
      const int ht = tid - 32;
      const bool do_w = cta < 96;
      unsigned tk = 0;
      if (ht == 32) tk = atomicAdd(&g_ticket, 1u);
      cluster_wait();
      if (c.warp == 1 && elect_one()) {
        mbar_expect_tx(c.bar(B_ROWS), 20480 + 12800);
        bulk_load(sbuf + 20480, x + (size_t)cta * 16 * DM, 20480, c.bar(B_ROWS));
        bulk_load(sbuf + 40960, (cta < 64 ? hre : him) + (size_t)(cta & 63) * 10 * DM, 12800, c.bar(B_ROWS));
        if (do_w) {
          mbar_expect_tx(c.bar(B_PRE), 20480);
          #pragma unroll
          for (int i = 0; i < 4; i++) tma_load(sbuf + i * 5120, &maps.m[M_WCOL], c.bar(B_PRE), cta * 16, i * 160);
        }
      }
      if (ht == 32) { sts32(c.ext(X_TAG), __uint_as_float((tk >> 7) + 1u)); mbar_arrive(c.bar(B_TAG)); }
      __syncwarp();
      const unsigned tag = c.tag();
      if (do_w) {
        mbar_wait(c.bar(B_PRE), 0);
        if (ht == 0) TSTAMP1(33);
        float w[8];
        #pragma unroll
        for (int e = 0; e < 8; e++) w[e] = 0.f;
        #pragma unroll 1
        for (int i = ht; i < 1280; i += 192) {
          uint4 v = lds128u(sbuf + i * 16);
          uint4 u = lds128u(sbuf + min(i + 96, 1279) * 16);
          if (i + 96 >= 1280) u = make_uint4(0, 0, 0, 0);
          w[0] += bf_lo(v.x) + bf_lo(u.x); w[1] += bf_hi(v.x) + bf_hi(u.x); w[2] += bf_lo(v.y) + bf_lo(u.y); w[3] += bf_hi(v.y) + bf_hi(u.y);
          w[4] += bf_lo(v.z) + bf_lo(u.z); w[5] += bf_hi(v.z) + bf_hi(u.z); w[6] += bf_lo(v.w) + bf_lo(u.w); w[7] += bf_hi(v.w) + bf_hi(u.w);
        }
        __syncwarp();
        const bool u1 = c.lane & 2, u2 = c.lane & 4, u3 = c.lane & 8;
        float a4[4], a2[2], a1;
        #pragma unroll
        for (int e = 0; e < 4; e++) a4[e] = (u1 ? w[4 + e] : w[e]) + __shfl_xor_sync(0xffffffffu, u1 ? w[e] : w[4 + e], 2);
        #pragma unroll
        for (int e = 0; e < 2; e++) a2[e] = (u2 ? a4[2 + e] : a4[e]) + __shfl_xor_sync(0xffffffffu, u2 ? a4[e] : a4[2 + e], 4);
        a1 = (u3 ? a2[1] : a2[0]) + __shfl_xor_sync(0xffffffffu, u3 ? a2[0] : a2[1], 8);
        a1 += __shfl_xor_sync(0xffffffffu, a1, 16);
        const int col = (c.lane & 1) * 8 + (u1 ? 4 : 0) + (u2 ? 2 : 0) + (u3 ? 1 : 0);
        if (c.lane < 16) sts32(c.ext(X_RED) + (c.warp - 1) * 64 + col * 4, a1);
        named_sync(3, 96);
        if (ht < 16) st_tag1(&g_csum[2 * DM + cta * 16 + ht], tagged(lds32(c.ext(X_RED) + ht * 4) + lds32(c.ext(X_RED) + 64 + ht * 4) + lds32(c.ext(X_RED) + 128 + ht * 4), tag));
        if (ht == 0) TSTAMP1(35);
      }
      if (c.warp == 1) {
        #pragma unroll 1
        for (int job = 0; job < (isG ? 4 : 3); job++) {
          const bool last = job == (isG ? 3 : 2);
          if (last && isG) {
            #pragma unroll 1
            for (int sp = 0; sp < SPIN_MAX; sp++) { if (flag_get(FL_F + rb * 4 + ct) == tag) break; __nanosleep(POLL_NS); }
            fence_async_global();
            if (c.lane == 0) TSTAMP1(29);
          }
          mbar_wait(c.bar(B_STORE), job & 1);
          if (c.lane == 0) TSTAMP1(48 + job * 2);
          if (elect_one()) {
            int fl;
            if (last) {
              #pragma unroll
              for (int b = 0; b < 5; b++) tma_reduce_add(&maps.m[M_OUT], sbuf + b * 8192, ct * 160 + b * 32, row0, 1);
              fl = FL_F + rb * 4 + ct;
            } else {
              const CUtensorMap* tm = &maps.m[isG ? (job == 2 ? M_HT : M_Z2NT) : M_ABT];
              const int c0 = row0 + (isG ? 0 : job * SEQ), c1 = isG ? ct * 192 : ct * 160;
              const uint32_t bx = isG ? 192 * 128 : 160 * 128;
              tma_store(tm, sbuf, c0, c1, !(isG && job == 1));
              tma_store(tm, sbuf + bx, c0 + 64, c1, !(isG && job == 0));
              fl = isG ? (job == 2 ? FL_H + rb * 4 + ct : FL_Z2N + (ct * 2 + job) * 16 + rb) : FL_AB + (job * 4 + ct) * 16 + rb;
            }
            bulk_commit();
            if (last && isG) bulk_wait_read();
            else {
              bulk_wait_all();
              flag_set(fl, tag, 1);
              if (!isG && job == 1) {
                mbar_expect_tx(c.bar(B_XRES), 128 * 160 * 2);
                #pragma unroll
                for (int b = 0; b < 5; b++) tma_load(sbuf + b * 8192, &maps.m[M_XRES], c.bar(B_XRES), ct * 160 + b * 32, row0);
                mbar_wait(c.bar(B_XRES), 0);
                #pragma unroll
                for (int b = 0; b < 5; b++) tma_store(&maps.m[M_OUT], sbuf + b * 8192, ct * 160 + b * 32, row0, 1);
                bulk_commit();
                bulk_wait_all();
              }
              if (!(isG && job == 0)) mbar_arrive(c.bar(B_SFREE));
            }
          }
          __syncwarp();
          if (c.lane == 0) TSTAMP1(49 + job * 2);
        }
      }
    }
  } else {
    asm volatile("setmaxnreg.inc.sync.aligned.u32 232;");
    const uint32_t a0 = stage_t_addr(c);
    cluster_wait();
    auto staged = [&](int live) { fence_async_smem(); mbar_arrive_if(c.bar(B_STORE), live); };

    auto prepare = [&]() {
      TSTAMP(36);
      const unsigned tag = c.tag();
      mbar_wait(c.bar(B_ROWS), 0);
      #pragma unroll 1
      for (int set = 0; set < 2; set++) {
        const int row = set * 16 + min(tid >> 3, set == 1 ? 9 : 15);
        const uint32_t ra = sbuf + 20480 + row * 1280 + (tid & 7) * 16;
        float s0 = 0.f, s1 = 0.f, q0 = 0.f, q1 = 0.f;
        #pragma unroll 1
        for (int i = 0; i < 10; i += 5) {
          uint4 v[5];
          #pragma unroll
          for (int u = 0; u < 5; u++) v[u] = lds128u(ra + (i + u) * 128);
          #pragma unroll
          for (int u = 0; u < 5; u++) {
            uint32_t w[4] = {v[u].x, v[u].y, v[u].z, v[u].w};
            #pragma unroll
            for (int e = 0; e < 4; e++) {
              float lo = bf_lo(w[e]), hi = bf_hi(w[e]);
              s0 += lo; s1 += hi; q0 = fmaf(lo, lo, q0); q1 = fmaf(hi, hi, q1);
            }
          }
        }
        float sm = s0 + s1, sq = q0 + q1;
        #pragma unroll
        for (int o = 1; o < 8; o <<= 1) { sm += __shfl_xor_sync(0xffffffffu, sm, o); sq += __shfl_xor_sync(0xffffffffu, sq, o); }
        const float mean = sm * (1.0f / DM);
        st_tag2(&g_rowstat[(cta * 16 + (tid >> 3)) * 2], tagged(mean, tag), tagged(rsqrtf(fmaxf(sq * (1.0f / DM) - mean * mean, 0.f) + LN_EPS), tag), set == 0 && (tid & 7) == 0);
        if (set == 1 && (tid & 7) == 0 && tid < 80) st_tag1(&g_csum[cta * 10 + (tid >> 3)], tagged(sm, tag));
      }
      TSTAMP(2);
      named_sync(2, 128);
      const int NT = isG ? 192 : 160;
      const float bias = __bfloat162float(bsp[row0 + tid]);
      uint4 rs; uint2 cs[3];
      #pragma unroll 1
      for (int sp = 0; sp < SPIN_MAX; sp++) {
        rs = ld_tag2(&g_rowstat[(row0 + tid) * 2]);
        bool ok = rs.y == tag && rs.w == tag;
        #pragma unroll
        for (int i = 0; i < 3; i++) {
          const int ii = min(tid + i * 128, 2 * NT - 1), t = ii >= NT, n = ii - t * NT;
          cs[i] = ld_tag1(&g_csum[(isG ? 2 * DM + (t ? 0 : FH) : t * DM) + ct * NT + n]);
          ok = ok && cs[i].y == tag;
        }
        if (ok) break;
        __nanosleep(2 * POLL_NS);
      }
      float m1, m2, m3;
      split3(-__uint_as_float(rs.x), m1, m2, m3);
      sts128u(c.ext(X_A) + tid * 16, pack_bf16(m1, m1), pack_bf16(m2, m1), pack_bf16(m2, m3), pack_bf16(bias, 0.f), 1);
      sts128u(c.ext(X_Z) + tid * 16, 0, 0, 0, 0, 1);
      sts32(c.ext(X_RSTD) + tid * 4, __uint_as_float(rs.z));
      #pragma unroll
      for (int i = 0; i < 3; i++) {
        const int ii = min(tid + i * 128, 2 * NT - 1), t = ii >= NT, n = ii - t * NT;
        split3(__uint_as_float(cs[i].x), m1, m2, m3);
        sts128u(c.ext(X_B) + t * 3072 + n * 16, pack_bf16(m1, m2), pack_bf16(m1, m3), pack_bf16(m2, m1), 0, 1);
      }
      sts128u(c.ext(X_ONES) + (tid & 7) * 16, 0, 0, 0, 0x00003F80u, tid < 8);
      fence_async_smem();
      mbar_arrive(c.bar(B_TAB));
      TSTAMP(3);
      mbar_wait(c.bar(B_TAB), 0);
    };

    const uint32_t rs_a = c.ext(X_RSTD) + (c.warp * 16 + (c.lane >> 2)) * 4;
    float acc[2][80];
    if (!isG) {
      auto epi_ab = [&](float sgn, int live) {
        #pragma unroll
        for (int mb = 0; mb < 2; mb++) {
          const float s0 = sgn * lds32(rs_a + mb * 256), s1 = sgn * lds32(rs_a + mb * 256 + 32);
          #pragma unroll
          for (int hf = 0; hf < 2; hf++) {
            if (live || c.warp == mb * 2 + hf) {
              #pragma unroll
              for (int j = hf * 10; j < hf * 10 + 10; j += 2)
                stmatrix_x4_t(a0 + mb * (160 * 128) + j * 1024,
                              pack_bf16(acc[mb][4 * j + 0] * s0, acc[mb][4 * j + 1] * s0), pack_bf16(acc[mb][4 * j + 2] * s1, acc[mb][4 * j + 3] * s1),
                              pack_bf16(acc[mb][4 * j + 4] * s0, acc[mb][4 * j + 5] * s0), pack_bf16(acc[mb][4 * j + 6] * s1, acc[mb][4 * j + 7] * s1), live);
            }
          }
        }
        staged(live);
      };
      if (wg == 0) {
        mainloop<160, 0, 0, true>(c, acc, 0, 10, false, c.bar(B_TURN1));
        drain_ext<160>(c, acc, 9, c.ext(X_B), 128);
        TSTAMP(4);
      }
      epi_ab(1.0f, wg == 0);
      if (wg == 1) {
        prepare();
        mbar_wait(c.bar(B_TURN1), 0);
        first_ext<160>(c, acc, c.ext(X_B) + 3072, 128);
        mainloop<160, 0, 0, false>(c, acc, 10, 10, false, c.bar(B_TURN0));
        drain<160>(c, acc, 19);
        TSTAMP(8);
        mbar_wait(c.bar(B_SFREE), 0);
        epi_ab(-1.0f, 1);
      } else {
        mbar_wait(c.bar(B_TURN0), 0);
        TSTAMP(12);
        mainloop<160, 0, 0, true>(c, acc, 20, 64 - JSPLIT, false, 0);
        drain<160>(c, acc, 20 + 64 - JSPLIT - 1);
        TSTAMP(13);
        mbar_wait(c.bar(B_SFREE), 1);
      }
    } else {
      float acz[2][96];
      if (wg == 0) {
        mainloop<192, 0, 1, true>(c, acz, 0, 10, false, c.bar(B_TURN1));
        drain_ext<192>(c, acz, 9, c.ext(X_B), 128);
        TSTAMP(4);
      }
      {
        const int live = wg == 0;
        const unsigned tag = c.tag();
        u64* const zst = &g_z2stat[(row0 + c.warp * 16 + (c.lane >> 2)) * 8];
        #pragma unroll
        for (int mb = 0; mb < 2; mb++) {
          const float h0 = 0.5f * lds32(rs_a + mb * 256), h1 = 0.5f * lds32(rs_a + mb * 256 + 32);
          float s0 = 0.f, s1 = 0.f, q0 = 0.f, q1 = 0.f;
          #pragma unroll
          for (int hf = 0; hf < 2; hf++) {
            if (live || c.warp == mb * 2 + hf) {
              #pragma unroll
              for (int j = hf * 12; j < hf * 12 + 12; j++) {
                const float g0 = gelu_half(acz[mb][4 * j] * h0), g1 = gelu_half(acz[mb][4 * j + 1] * h0);
                const float g2 = gelu_half(acz[mb][4 * j + 2] * h1), g3 = gelu_half(acz[mb][4 * j + 3] * h1);
                acz[mb][4 * j] = g0; acz[mb][4 * j + 1] = g1; acz[mb][4 * j + 2] = g2; acz[mb][4 * j + 3] = g3;
                s0 += g0 + g1; s1 += g2 + g3;
                q0 = fmaf(g0, g0, q0); q0 = fmaf(g1, g1, q0); q1 = fmaf(g2, g2, q1); q1 = fmaf(g3, g3, q1);
              }
            }
          }
          const bool up = c.lane & 2;
          float sm = (up ? s1 : s0) + __shfl_xor_sync(0xffffffffu, up ? s0 : s1, 2);
          float sq = (up ? q1 : q0) + __shfl_xor_sync(0xffffffffu, up ? q0 : q1, 2);
          sm += __shfl_xor_sync(0xffffffffu, sm, 1); sq += __shfl_xor_sync(0xffffffffu, sq, 1);
          st_tag2(zst + (mb * 64 + (up ? 8 : 0)) * 8 + ct * 2, tagged(sm, tag), tagged(sq, tag), live && !(c.lane & 1));
          if (live) TSTAMP(5 + mb * 11);
        }
        #pragma unroll
        for (int mb = 0; mb < 2; mb++) {
          if (live || c.warp == mb * 2) {
            uint4 e0, e1;
            #pragma unroll 1
            for (int sp = 0; sp < SPIN_MAX; sp++) {
              e0 = ld_tag2(zst + mb * 512 + (c.lane & 3) * 2); e1 = ld_tag2(zst + mb * 512 + 64 + (c.lane & 3) * 2);
              const bool ok = e0.y == tag && e0.w == tag && e1.y == tag && e1.w == tag;
              if (__all_sync(0xffffffffu, ok) || !live) break;
              __nanosleep(POLL_NS);
            }
            float s0 = __uint_as_float(e0.x), q0 = __uint_as_float(e0.z), s1 = __uint_as_float(e1.x), q1 = __uint_as_float(e1.z);
            #pragma unroll
            for (int o = 1; o < 4; o <<= 1) {
              s0 += __shfl_xor_sync(0xffffffffu, s0, o); q0 += __shfl_xor_sync(0xffffffffu, q0, o);
              s1 += __shfl_xor_sync(0xffffffffu, s1, o); q1 += __shfl_xor_sync(0xffffffffu, q1, o);
            }
            s0 *= 1.0f / FH; s1 *= 1.0f / FH;
            const float r0 = rsqrtf(fmaxf(q0 * (1.0f / FH) - s0 * s0, 0.f) + LN_EPS), r1 = rsqrtf(fmaxf(q1 * (1.0f / FH) - s1 * s1, 0.f) + LN_EPS);
            const float o0 = -s0 * r0, o1 = -s1 * r1;
            if (live && mb == 0) TSTAMP(17);
            #pragma unroll
            for (int j = 0; j < 24; j += 2)
              stmatrix_x4_t(a0 + mb * (192 * 128) + j * 1024,
                            pack_bf16(fmaf(acz[mb][4 * j + 0], r0, o0), fmaf(acz[mb][4 * j + 1], r0, o0)), pack_bf16(fmaf(acz[mb][4 * j + 2], r1, o1), fmaf(acz[mb][4 * j + 3], r1, o1)),
                            pack_bf16(fmaf(acz[mb][4 * j + 4], r0, o0), fmaf(acz[mb][4 * j + 5], r0, o0)), pack_bf16(fmaf(acz[mb][4 * j + 6], r1, o1), fmaf(acz[mb][4 * j + 7], r1, o1)), live);
            staged(live);
          }
        }
      }
      if (wg == 1) {
        prepare();
        mbar_wait(c.bar(B_TURN1), 0);
        first_ext<192>(c, acz, c.ext(X_B) + 3072, 128);
        mainloop<192, 0, 1, false>(c, acz, 10, 10, false, c.bar(B_TURN0));
        drain<192>(c, acz, 19);
        TSTAMP(8);
        mbar_wait(c.bar(B_SFREE), 0);
        #pragma unroll
        for (int mb = 0; mb < 2; mb++)
          #pragma unroll
          for (int j = 0; j < 24; j += 2)
            stmatrix_x4_t(a0 + mb * (192 * 128) + j * 1024,
                          pack_bf16(acz[mb][4 * j + 0], acz[mb][4 * j + 1]), pack_bf16(acz[mb][4 * j + 2], acz[mb][4 * j + 3]),
                          pack_bf16(acz[mb][4 * j + 4], acz[mb][4 * j + 5]), pack_bf16(acz[mb][4 * j + 6], acz[mb][4 * j + 7]), 1);
      } else {
        mbar_wait(c.bar(B_TURN0), 0);
        TSTAMP(12);
        first_ext<192>(c, acz, c.ext(X_ONES), 0);
        mainloop<192, 0, 0, false>(c, acz, 20, 32, false, c.bar(B_TURN1));
        drain<192>(c, acz, 51);
        TSTAMP(13);
        mbar_wait(c.bar(B_Z1RDY), 0);
      }
      {
        const int live = wg == 0;
        #pragma unroll
        for (int g = 0; g < 6; g++) {
          uint32_t z[4][4];
          #pragma unroll
          for (int i = 0; i < 4; i++) ldmatrix_x4_t(a0 + (g * 4 + i) * 2048, z[i]);
          #pragma unroll
          for (int i = 0; i < 4; i++) {
            const float* v = &acz[g / 3][((g % 3) * 4 + i) * 8];
            stmatrix_x4_t(a0 + (g * 4 + i) * 2048, mul_bf16x2(z[i][0], pack_bf16(v[0], v[1])), mul_bf16x2(z[i][1], pack_bf16(v[2], v[3])),
                          mul_bf16x2(z[i][2], pack_bf16(v[4], v[5])), mul_bf16x2(z[i][3], pack_bf16(v[6], v[7])), live);
          }
        }
        staged(live);
      }
      if (wg == 1) {
        named_sync(2, 128);
        const uint32_t e0 = sbuf + (tid >> 3) * 128 + (((tid & 7) ^ ((tid >> 3) & 7)) << 4);
        #pragma unroll 1
        for (int mb = 0; mb < 2; mb++) {
          const float4 u = lds128(c.ext(X_RSTD) + mb * 256 + (tid & 7) * 32), v = lds128(c.ext(X_RSTD) + mb * 256 + (tid & 7) * 32 + 16);
          const float hr[8] = {0.5f * u.x, 0.5f * u.y, 0.5f * u.z, 0.5f * u.w, 0.5f * v.x, 0.5f * v.y, 0.5f * v.z, 0.5f * v.w};
          #pragma unroll 1
          for (int i = 0; i < 12; i += 3) {
            uint4 v3[3];
            #pragma unroll
            for (int k = 0; k < 3; k++) v3[k] = lds128u(e0 + mb * (192 * 128) + (i + k) * 2048);
            #pragma unroll
            for (int k = 0; k < 3; k++) {
              uint32_t w[4] = {v3[k].x, v3[k].y, v3[k].z, v3[k].w};
              #pragma unroll
              for (int e = 0; e < 4; e++) w[e] = pack_bf16(gelu_half(bf_lo(w[e]) * hr[2 * e]), gelu_half(bf_hi(w[e]) * hr[2 * e + 1]));
              sts128u(e0 + mb * (192 * 128) + (i + k) * 2048, w[0], w[1], w[2], w[3], 1);
            }
          }
        }
        mbar_arrive(c.bar(B_Z1RDY));
        TSTAMP(11);
        mbar_wait(c.bar(B_TURN1), 1);
        mainloop<160, 0, 0, true>(c, acc, 52, JSPLIT, false, 0);
        TSTAMP(15);
        mainloop<160, 1, 1, false>(c, acc, 52 + JSPLIT, 12, true, 0);
        drain<160>(c, acc, 52 + JSPLIT + 11);
        TSTAMP(9);
        mbar_wait(c.bar(B_SFREE), 1);
      }
    }
    {
      const int live = wg == (isG ? 1 : 0);
      const int mi = c.lane >> 3, rl = c.warp * 16 + (mi & 1) * 8 + (c.lane & 7);
      const uint32_t o0 = sbuf + rl * 64 + (((mi >> 1) ^ ((rl >> 1) & 3)) << 4);
      #pragma unroll
      for (int mb = 0; mb < 2; mb++)
        #pragma unroll
        for (int j = 0; j < 20; j += 2)
          stmatrix_x4((o0 ^ ((j & 2) << 4)) + (j >> 2) * 8192 + mb * 4096,
                      pack_bf16(acc[mb][4 * j + 0], acc[mb][4 * j + 1]), pack_bf16(acc[mb][4 * j + 2], acc[mb][4 * j + 3]),
                      pack_bf16(acc[mb][4 * j + 4], acc[mb][4 * j + 5]), pack_bf16(acc[mb][4 * j + 6], acc[mb][4 * j + 7]), live);
      staged(live);
    }
  }
  __syncwarp();
  cluster_arrive();
  cluster_wait();
  if (threadIdx.x == 0) { TSTAMP1(21); TSTAMP_G(31); }
}

typedef CUresult (*EncodeFn)(CUtensorMap*, CUtensorMapDataType, cuuint32_t, void*, const cuuint64_t*, const cuuint64_t*,
                             const cuuint32_t*, const cuuint32_t*, CUtensorMapInterleave, CUtensorMapSwizzle,
                             CUtensorMapL2promotion, CUtensorMapFloatOOBfill);

void make_map(EncodeFn enc, CUtensorMap* m, const void* p, int rows, int cols, int box_rows, int box_cols, CUtensorMapSwizzle sw) {
  cuuint64_t gd[2] = {(cuuint64_t)cols, (cuuint64_t)rows};
  cuuint64_t gs[1] = {(cuuint64_t)cols * 2};
  cuuint32_t bd[2] = {(cuuint32_t)box_cols, (cuuint32_t)box_rows};
  cuuint32_t es[2] = {1, 1};
  enc(m, CU_TENSOR_MAP_DATA_TYPE_BFLOAT16, 2, (void*)p, gd, gs, bd, es, CU_TENSOR_MAP_INTERLEAVE_NONE, sw,
      CU_TENSOR_MAP_L2_PROMOTION_L2_256B, CU_TENSOR_MAP_FLOAT_OOB_FILL_NONE);
}

}

extern "C" void kernel_launch(void* const* d_in, const int* in_sizes, int n_in, void* d_out, int out_size) {
  const __nv_bfloat16* x = (const __nv_bfloat16*)d_in[0];
  const __nv_bfloat16* sre = (const __nv_bfloat16*)d_in[1];
  const __nv_bfloat16* sim = (const __nv_bfloat16*)d_in[2];
  const __nv_bfloat16* hre = (const __nv_bfloat16*)d_in[3];
  const __nv_bfloat16* him = (const __nv_bfloat16*)d_in[4];
  const __nv_bfloat16* win = (const __nv_bfloat16*)d_in[6];
  const __nv_bfloat16* wsp = (const __nv_bfloat16*)d_in[7];
  const __nv_bfloat16* bsp = (const __nv_bfloat16*)d_in[8];
  const __nv_bfloat16* wout = (const __nv_bfloat16*)d_in[9];

  void* fn = nullptr;
  cudaDriverEntryPointQueryResult qr;
  cudaGetDriverEntryPoint("cuTensorMapEncodeTiled", &fn, cudaEnableDefault, &qr);
  EncodeFn enc = (EncodeFn)fn;
  void *p_abT, *p_z2nT, *p_hT;
  cudaGetSymbolAddress(&p_abT, g_abT);
  cudaGetSymbolAddress(&p_z2nT, g_z2nT);
  cudaGetSymbolAddress(&p_hT, g_hT);
  Maps m;
  const CUtensorMapSwizzle S128 = CU_TENSOR_MAP_SWIZZLE_128B, S64 = CU_TENSOR_MAP_SWIZZLE_64B;
  make_map(enc, &m.m[M_X], x, SEQ, DM, 64, 64, S128);
  make_map(enc, &m.m[M_HRE], hre, DM, DM, 160, 64, S128);
  make_map(enc, &m.m[M_HIM], him, DM, DM, 160, 64, S128);
  make_map(enc, &m.m[M_WIN], win, DM, 2 * FH, 64, 64, S128);
  make_map(enc, &m.m[M_SRE], sre, SEQ, SEQ, 64, 64, S128);
  make_map(enc, &m.m[M_SIM], sim, SEQ, SEQ, 64, 64, S128);
  make_map(enc, &m.m[M_WSP], wsp, SEQ, SEQ, 64, 64, S128);
  make_map(enc, &m.m[M_ABT], p_abT, DM, 2 * SEQ, 160, 64, S128);
  make_map(enc, &m.m[M_Z2NT], p_z2nT, FH, SEQ, 192, 64, S128);
  make_map(enc, &m.m[M_HT], p_hT, FH, SEQ, 192, 64, S128);
  make_map(enc, &m.m[M_HTLD], p_hT, FH, SEQ, 64, 64, S128);
  make_map(enc, &m.m[M_WOUT], wout, FH, DM, 64, 64, S128);
  make_map(enc, &m.m[M_OUT], d_out, SEQ, DM, 128, 32, S64);
  make_map(enc, &m.m[M_XRES], x, SEQ, DM, 128, 32, S64);
  make_map(enc, &m.m[M_WCOL], win, DM, 2 * FH, 160, 16, CU_TENSOR_MAP_SWIZZLE_NONE);
  cudaFuncSetAttribute(fused_kernel, cudaFuncAttributeMaxDynamicSharedMemorySize, SMEM_BYTES);
  fused_kernel<<<NCTA, 384, SMEM_BYTES>>>(m, x, hre, him, sre, sim, wsp, bsp, wout);
}
```

```cpp
#include <cuda.h>
#include <cuda_runtime.h>
#include <cuda_bf16.h>
#include <stdint.h>

extern __shared__ __align__(1024) uint8_t smem_raw[];

#define EARLY_NS 0
namespace {

constexpr int SEQ = 2048, DM = 640, FH = 768;
constexpr int STAGES = 4;
constexpr int STAGE_BYTES = 40960;
constexpr int A_BYTES = 16384;
constexpr int SBUF_OFF = STAGES * STAGE_BYTES;
constexpr int EXT_OFF = SBUF_OFF + 49152;
constexpr int X_ID = 0, X_A = 8192, X_Z = 10240, X_ONES = 12288, X_TAG = 12416;
constexpr int BAR_OFF = EXT_OFF + 12544;
constexpr int SMEM_BYTES = BAR_OFF + 512;
#define JSPLIT 4
static_assert(JSPLIT % 2 == 0 || true, "the F-CTAs split the rest evenly");
#define YSOLO 4
constexpr int NY = 16 + (32 - JSPLIT - YSOLO) / 2;
constexpr int IT_F = 54;
constexpr int IT_Y = IT_F + JSPLIT + 12;
constexpr int STAGE2_BYTES = 32768 + 160 * 128;
#define ST_SPLIT 1
constexpr int NCTA = 128;
constexpr float LN_EPS = 1e-5f;
static_assert(SMEM_BYTES <= 232448, "smem");

enum { M_X, M_HRE, M_HIM, M_WIN, M_SRE2, M_SIM2, M_SIM, M_WSP, M_ABT, M_Z2NT, M_HT, M_HTLD, M_WOUT, M_ABTS, M_Z2NTS, M_OUT, M_XB, M_COUNT };
struct Maps { CUtensorMap m[M_COUNT]; };

typedef unsigned long long u64;
__device__ __align__(1024) __nv_bfloat16 g_xn[SEQ * DM];
__device__ __align__(1024) uint4 g_y[2 * 64 * 2560];
__device__ __align__(1024) __nv_bfloat16 g_abT[DM * 2 * SEQ];
__device__ __align__(1024) __nv_bfloat16 g_z2nT[FH * SEQ];
__device__ __align__(1024) __nv_bfloat16 g_hT[FH * SEQ];
__device__ __align__(128) u64 g_z2stat[4 * SEQ * 2];
enum { FL_AB = 0, FL_Z2N = 128, FL_H = 256, FL_F = 320, FL_XN = 448, FL_COUNT = 576 };
__device__ __align__(128) unsigned g_flags[FL_COUNT * 16];
__device__ unsigned g_ticket;

#define TSTAMP(id)
#define TSTAMP1(id)
#define TSTAMP_G(id)

__device__ __forceinline__ uint32_t smem_u32(const void* p) { return (uint32_t)__cvta_generic_to_shared(p); }
__device__ __forceinline__ void mbar_init(uint32_t bar, uint32_t cnt) { asm volatile("mbarrier.init.shared::cta.b64 [%0], %1;" :: "r"(bar), "r"(cnt) : "memory"); }
__device__ __forceinline__ void mbar_expect_tx(uint32_t bar, uint32_t bytes) { asm volatile("mbarrier.arrive.expect_tx.shared::cta.b64 _, [%0], %1;" :: "r"(bar), "r"(bytes) : "memory"); }
__device__ __forceinline__ void mbar_arrive(uint32_t bar) { asm volatile("mbarrier.arrive.shared::cta.b64 _, [%0];" :: "r"(bar) : "memory"); }
__device__ __forceinline__ void mbar_arrive_if(uint32_t bar, int live) {
  asm volatile("{\n.reg .pred p;\nsetp.ne.b32 p, %1, 0;\n@p mbarrier.arrive.shared::cta.b64 _, [%0];\n}\n" :: "r"(bar), "r"(live) : "memory");
}
__device__ __forceinline__ void mbar_arrive_cluster(uint32_t bar, uint32_t cta) {
  asm volatile("{\n.reg .b32 ra;\nmapa.shared::cluster.u32 ra, %0, %1;\nmbarrier.arrive.shared::cluster.b64 _, [ra];\n}\n" :: "r"(bar), "r"(cta) : "memory");
}
__device__ __forceinline__ void mbar_wait(uint32_t bar, uint32_t parity) {
  asm volatile("{\n.reg .pred p;\n.reg .u32 c;\nmov.u32 c, 0;\nLAB_WAIT:\n"
               "mbarrier.try_wait.parity.shared::cta.b64 p, [%0], %1;\n@p bra LAB_DONE;\n"
               "add.u32 c, c, 1;\nsetp.lt.u32 p, c, 20000;\n@p bra LAB_WAIT;\nLAB_DONE:\n}\n" :: "r"(bar), "r"(parity) : "memory");
}
__device__ __forceinline__ uint32_t late_drain(uint32_t bar, uint32_t parity, uint32_t ns) {
  uint32_t late;
  asm volatile("{\n.reg .pred p;\nmbarrier.try_wait.parity.shared::cta.b64 p, [%1], %2, %3;\nvote.sync.all.pred p, p, 0xffffffff;\n"
               "selp.u32 %0, 0, 1, p;\n@p bra.uni LAB_OK;\nwgmma.wait_group.sync.aligned 0;\nLAB_OK:\n}\n" : "=r"(late) : "r"(bar), "r"(parity), "r"(ns) : "memory");
  return late;
}
__device__ __forceinline__ void tma_load(uint32_t dst, const CUtensorMap* tm, uint32_t bar, int c0, int c1) {
  asm volatile("cp.async.bulk.tensor.2d.shared::cluster.global.mbarrier::complete_tx::bytes [%0], [%1, {%3, %4}], [%2];"
    :: "r"(dst), "l"((uint64_t)tm), "r"(bar), "r"(c0), "r"(c1) : "memory");
}
__device__ __forceinline__ void tma_load_mc(uint32_t dst, const CUtensorMap* tm, uint32_t bar, int c0, int c1) {
  asm volatile("cp.async.bulk.tensor.2d.shared::cluster.global.mbarrier::complete_tx::bytes.multicast::cluster [%0], [%1, {%3, %4}], [%2], %5;"
    :: "r"(dst), "l"((uint64_t)tm), "r"(bar), "r"(c0), "r"(c1), "h"((uint16_t)3) : "memory");
}
__device__ __forceinline__ void bulk_load(uint32_t dst, const void* src, uint32_t bytes, uint32_t bar) {
  asm volatile("cp.async.bulk.shared::cluster.global.mbarrier::complete_tx::bytes [%0], [%1], %2, [%3];"
    :: "r"(dst), "l"((uint64_t)src), "r"(bytes), "r"(bar) : "memory");
}
__device__ __forceinline__ void tma_store(const CUtensorMap* tm, uint32_t src, int c0, int c1, int live) {
  asm volatile("{\n.reg .pred p;\nsetp.ne.b32 p, %4, 0;\n@p cp.async.bulk.tensor.2d.global.shared::cta.bulk_group [%0, {%2, %3}], [%1];\n}\n"
    :: "l"((uint64_t)tm), "r"(src), "r"(c0), "r"(c1), "r"(live) : "memory");
}
__device__ __forceinline__ void tma_reduce_add(const CUtensorMap* tm, uint32_t src, int c0, int c1, int live) {
  asm volatile("{\n.reg .pred p;\nsetp.ne.b32 p, %4, 0;\n@p cp.reduce.async.bulk.tensor.2d.global.shared::cta.add.bulk_group [%0, {%2, %3}], [%1];\n}\n"
    :: "l"((uint64_t)tm), "r"(src), "r"(c0), "r"(c1), "r"(live) : "memory");
}
__device__ __forceinline__ void bulk_store(void* dst, uint32_t src, uint32_t bytes) {
  asm volatile("cp.async.bulk.global.shared::cta.bulk_group [%0], [%1], %2;" :: "l"(dst), "r"(src), "r"(bytes) : "memory");
}
__device__ __forceinline__ void bulk_commit() { asm volatile("cp.async.bulk.commit_group;" ::: "memory"); }
__device__ __forceinline__ void bulk_wait_read() { asm volatile("cp.async.bulk.wait_group.read 0;" ::: "memory"); }
__device__ __forceinline__ void bulk_wait_all() { asm volatile("cp.async.bulk.wait_group 0;" ::: "memory"); }
__device__ __forceinline__ void l2_prefetch(const void* p, uint32_t bytes) {
  asm volatile("cp.async.bulk.prefetch.L2.global [%0], %1;" :: "l"((uint64_t)p), "r"(bytes) : "memory");
}
__device__ __forceinline__ void tma_prefetch(const CUtensorMap* tm, int c0, int c1) {
  asm volatile("cp.async.bulk.prefetch.tensor.2d.L2.global [%0, {%1, %2}];" :: "l"((uint64_t)tm), "r"(c0), "r"(c1) : "memory");
}
__device__ __forceinline__ void cp_async16(uint32_t dst, const void* src) {
  asm volatile("cp.async.cg.shared.global [%0], [%1], 16;" :: "r"(dst), "l"(src) : "memory");
}
__device__ __forceinline__ void cp_async_wait() { asm volatile("cp.async.wait_all;" ::: "memory"); }
__device__ __forceinline__ void prefetch_l2(const void* p) { asm volatile("prefetch.global.L2 [%0];" :: "l"(p)); }
__device__ __forceinline__ void prefetch_tmap(const CUtensorMap* tm) { asm volatile("prefetch.tensormap [%0];" :: "l"((uint64_t)tm) : "memory"); }
__device__ __forceinline__ void fence_async_smem() { asm volatile("fence.proxy.async.shared::cta;" ::: "memory"); }
__device__ __forceinline__ void fence_async_global() { asm volatile("fence.proxy.async.global;" ::: "memory"); }
__device__ __forceinline__ void wgmma_fence() { asm volatile("wgmma.fence.sync.aligned;" ::: "memory"); }
__device__ __forceinline__ void wgmma_commit() { asm volatile("wgmma.commit_group.sync.aligned;" ::: "memory"); }
template<int N> __device__ __forceinline__ void wgmma_wait() { asm volatile("wgmma.wait_group.sync.aligned %0;" :: "n"(N) : "memory"); }
__device__ __forceinline__ void cluster_arrive() { asm volatile("barrier.cluster.arrive.relaxed.aligned;" ::: "memory"); }
__device__ __forceinline__ void cluster_wait() { asm volatile("barrier.cluster.wait.acquire.aligned;" ::: "memory"); }
__device__ __forceinline__ bool elect_one() {
  uint32_t p; asm volatile("{\n.reg .pred p;\nelect.sync _|p, 0xffffffff;\nselp.u32 %0, 1, 0, p;\n}\n" : "=r"(p)); return p;
}
__device__ __forceinline__ void named_sync(int id, int n) { asm volatile("bar.sync %0, %1;" :: "r"(id), "r"(n) : "memory"); }
__device__ __forceinline__ void stmatrix_x4(uint32_t addr, uint32_t r0, uint32_t r1, uint32_t r2, uint32_t r3, int live) {
  asm volatile("{\n.reg .pred p;\nsetp.ne.b32 p, %5, 0;\n@p stmatrix.sync.aligned.m8n8.x4.shared.b16 [%0], {%1, %2, %3, %4};\n}\n"
    :: "r"(addr), "r"(r0), "r"(r1), "r"(r2), "r"(r3), "r"(live) : "memory");
}
__device__ __forceinline__ void stmatrix_x4_t(uint32_t addr, uint32_t r0, uint32_t r1, uint32_t r2, uint32_t r3, int live) {
  asm volatile("{\n.reg .pred p;\nsetp.ne.b32 p, %5, 0;\n@p stmatrix.sync.aligned.m8n8.x4.trans.shared.b16 [%0], {%1, %2, %3, %4};\n}\n"
    :: "r"(addr), "r"(r0), "r"(r1), "r"(r2), "r"(r3), "r"(live) : "memory");
}
__device__ __forceinline__ void ldmatrix_x4(uint32_t addr, uint32_t (&r)[4], int live) {
  asm volatile("{\n.reg .pred p;\nsetp.ne.b32 p, %5, 0;\n@p ldmatrix.sync.aligned.m8n8.x4.shared.b16 {%0, %1, %2, %3}, [%4];\n}\n"
    : "=r"(r[0]), "=r"(r[1]), "=r"(r[2]), "=r"(r[3]) : "r"(addr), "r"(live) : "memory");
}
__device__ __forceinline__ void ldmatrix_x4_t(uint32_t addr, uint32_t (&r)[4], int live) {
  asm volatile("{\n.reg .pred p;\nsetp.ne.b32 p, %5, 0;\n@p ldmatrix.sync.aligned.m8n8.x4.trans.shared.b16 {%0, %1, %2, %3}, [%4];\n}\n"
    : "=r"(r[0]), "=r"(r[1]), "=r"(r[2]), "=r"(r[3]) : "r"(addr), "r"(live) : "memory");
}
__device__ __forceinline__ uint4 lds128u_if(uint32_t addr, int live) {
  uint4 v;
  asm volatile("{\n.reg .pred p;\nsetp.ne.b32 p, %5, 0;\n@p ld.shared.v4.u32 {%0, %1, %2, %3}, [%4];\n}\n" : "=r"(v.x), "=r"(v.y), "=r"(v.z), "=r"(v.w) : "r"(addr), "r"(live) : "memory");
  return v;
}
__device__ __forceinline__ void sts128u(uint32_t addr, uint32_t a, uint32_t b, uint32_t c, uint32_t d, int live) {
  asm volatile("{\n.reg .pred p;\nsetp.ne.b32 p, %5, 0;\n@p st.shared.v4.b32 [%0], {%1, %2, %3, %4};\n}\n" :: "r"(addr), "r"(a), "r"(b), "r"(c), "r"(d), "r"(live) : "memory");
}
__device__ __forceinline__ void stg128(void* p, uint4 v, int live) {
  asm volatile("{\n.reg .pred p;\nsetp.ne.b32 p, %5, 0;\n@p st.global.v4.b32 [%0], {%1, %2, %3, %4};\n}\n" :: "l"(p), "r"(v.x), "r"(v.y), "r"(v.z), "r"(v.w), "r"(live) : "memory");
}
__device__ __forceinline__ float4 lds128(uint32_t addr) {
  float4 v; asm volatile("ld.shared.v4.f32 {%0, %1, %2, %3}, [%4];" : "=f"(v.x), "=f"(v.y), "=f"(v.z), "=f"(v.w) : "r"(addr) : "memory"); return v;
}
__device__ __forceinline__ uint4 lds128u(uint32_t addr) {
  uint4 v; asm volatile("ld.shared.v4.u32 {%0, %1, %2, %3}, [%4];" : "=r"(v.x), "=r"(v.y), "=r"(v.z), "=r"(v.w) : "r"(addr) : "memory"); return v;
}
__device__ __forceinline__ float2 lds64(uint32_t addr) {
  float2 v; asm volatile("ld.shared.v2.f32 {%0, %1}, [%2];" : "=f"(v.x), "=f"(v.y) : "r"(addr) : "memory"); return v;
}
__device__ __forceinline__ void sts64(uint32_t addr, float a, float b, int live) {
  asm volatile("{\n.reg .pred p;\nsetp.ne.b32 p, %3, 0;\n@p st.shared.v2.f32 [%0], {%1, %2};\n}\n" :: "r"(addr), "f"(a), "f"(b), "r"(live) : "memory");
}
__device__ __forceinline__ void sts32(uint32_t addr, float a) { asm volatile("st.shared.f32 [%0], %1;" :: "r"(addr), "f"(a) : "memory"); }
__device__ __forceinline__ float lds32(uint32_t addr) { float v; asm volatile("ld.shared.f32 %0, [%1];" : "=f"(v) : "r"(addr) : "memory"); return v; }
__device__ __forceinline__ uint32_t pack_bf16(float lo, float hi) {
  uint32_t r; asm("cvt.rn.bf16x2.f32 %0, %1, %2;" : "=r"(r) : "f"(hi), "f"(lo)); return r;
}
__device__ __forceinline__ uint32_t mul_bf16x2(uint32_t a, uint32_t b) {
  uint32_t r; asm("mul.rn.bf16x2 %0, %1, %2;" : "=r"(r) : "r"(a), "r"(b)); return r;
}
__device__ __forceinline__ uint32_t add_bf16x2(uint32_t a, uint32_t b) {
  uint32_t r; asm("add.rn.bf16x2 %0, %1, %2;" : "=r"(r) : "r"(a), "r"(b)); return r;
}
__device__ __forceinline__ float bf_lo(uint32_t v) { return __uint_as_float(v << 16); }
__device__ __forceinline__ float bf_hi(uint32_t v) { return __uint_as_float(v & 0xffff0000u); }
__device__ __forceinline__ float bf_round(float v) { return bf_lo(pack_bf16(v, 0.f)); }

__device__ __forceinline__ u64 tagged(float v, unsigned tag) { return ((u64)tag << 32) | __float_as_uint(v); }
__device__ __forceinline__ void st_tag1(u64* p, u64 a, int live) {
  asm volatile("{\n.reg .pred p;\nsetp.ne.b32 p, %2, 0;\n@p st.relaxed.gpu.global.b64 [%0], %1;\n}\n" :: "l"(p), "l"(a), "r"(live) : "memory");
}
__device__ __forceinline__ void st_tag2(u64* p, u64 a, u64 b, int live) {
  asm volatile("{\n.reg .pred p;\nsetp.ne.b32 p, %3, 0;\n@p st.relaxed.gpu.global.v2.b64 [%0], {%1, %2};\n}\n" :: "l"(p), "l"(a), "l"(b), "r"(live) : "memory");
}
__device__ __forceinline__ uint2 ld_tag1(const u64* p) {
  u64 a; asm volatile("ld.relaxed.gpu.global.b64 %0, [%1];" : "=l"(a) : "l"(p) : "memory");
  return make_uint2((uint32_t)a, (uint32_t)(a >> 32));
}
__device__ __forceinline__ uint4 ld_tag2(const u64* p, int live) {
  u64 a = 0, b = 0;
  asm volatile("{\n.reg .pred p;\nsetp.ne.b32 p, %3, 0;\n@p ld.relaxed.gpu.global.v2.b64 {%0, %1}, [%2];\n}\n" : "+l"(a), "+l"(b) : "l"(p), "r"(live) : "memory");
  return make_uint4((uint32_t)a, (uint32_t)(a >> 32), (uint32_t)b, (uint32_t)(b >> 32));
}
__device__ __forceinline__ void flag_set(int id, unsigned tag, int live) {
  asm volatile("{\n.reg .pred p;\nsetp.ne.b32 p, %2, 0;\n@p st.relaxed.gpu.global.u32 [%0], %1;\n}\n" :: "l"(g_flags + id * 16), "r"(tag), "r"(live) : "memory");
}
__device__ __forceinline__ unsigned flag_get(int id) {
  unsigned v; asm volatile("ld.acquire.gpu.global.u32 %0, [%1];" : "=r"(v) : "l"(g_flags + id * 16) : "memory"); return v;
}
constexpr int SPIN_MAX = 2000000;
#define PRE_AFTER 0
#define ST_GAP_F 400
#define ST_GAP_G 200
#define W_DELAY 0
#define PF_X 34000
#define TURN_AT 0
#define PF_W 2500
#define PF_START_G 7000
#define PF_STEP_G 1400
#define PF_START 7000
#define PF_STEP 1280
#define FLAG_SLEEP
#define POLL_NS 100

__device__ __forceinline__ float gelu2(float v) {
  const float K1 = 0.7978845608f, K2 = 0.7978845608f * 0.044715f;
  float a = v * fmaf(v * v, K2, K1);
  float t; asm("tanh.approx.f32 %0, %1;" : "=f"(t) : "f"(a));
  return fmaf(v, t, v);
}

template<int N, int TA, int TB> struct Wgmma;
template<int TA, int TB> struct Wgmma<160, TA, TB> {
  static __device__ __forceinline__ void mma(float (&d)[80], uint64_t da, uint64_t db, int scale_d) {
    asm volatile("{\n.reg .pred p;\nsetp.ne.b32 p, %82, 0;\n"
      "wgmma.mma_async.sync.aligned.m64n160k16.f32.bf16.bf16 {%0, %1, %2, %3, %4, %5, %6, %7, %8, %9, %10, %11, %12, %13, %14, %15, %16, %17, %18, %19, %20, %21, %22, %23, %24, %25, %26, %27, %28, %29, %30, %31, %32, %33, %34, %35, %36, %37, %38, %39, %40, %41, %42, %43, %44, %45, %46, %47, %48, %49, %50, %51, %52, %53, %54, %55, %56, %57, %58, %59, %60, %61, %62, %63, %64, %65, %66, %67, %68, %69, %70, %71, %72, %73, %74, %75, %76, %77, %78, %79}, %80, %81, p, 1, 1, %83, %84;\n}\n"
      : "+f"(d[0]), "+f"(d[1]), "+f"(d[2]), "+f"(d[3]), "+f"(d[4]), "+f"(d[5]), "+f"(d[6]), "+f"(d[7]), "+f"(d[8]), "+f"(d[9]), "+f"(d[10]), "+f"(d[11]), "+f"(d[12]), "+f"(d[13]), "+f"(d[14]), "+f"(d[15]), "+f"(d[16]), "+f"(d[17]), "+f"(d[18]), "+f"(d[19]), "+f"(d[20]), "+f"(d[21]), "+f"(d[22]), "+f"(d[23]), "+f"(d[24]), "+f"(d[25]), "+f"(d[26]), "+f"(d[27]), "+f"(d[28]), "+f"(d[29]), "+f"(d[30]), "+f"(d[31]), "+f"(d[32]), "+f"(d[33]), "+f"(d[34]), "+f"(d[35]), "+f"(d[36]), "+f"(d[37]), "+f"(d[38]), "+f"(d[39]), "+f"(d[40]), "+f"(d[41]), "+f"(d[42]), "+f"(d[43]), "+f"(d[44]), "+f"(d[45]), "+f"(d[46]), "+f"(d[47]), "+f"(d[48]), "+f"(d[49]), "+f"(d[50]), "+f"(d[51]), "+f"(d[52]), "+f"(d[53]), "+f"(d[54]), "+f"(d[55]), "+f"(d[56]), "+f"(d[57]), "+f"(d[58]), "+f"(d[59]), "+f"(d[60]), "+f"(d[61]), "+f"(d[62]), "+f"(d[63]), "+f"(d[64]), "+f"(d[65]), "+f"(d[66]), "+f"(d[67]), "+f"(d[68]), "+f"(d[69]), "+f"(d[70]), "+f"(d[71]), "+f"(d[72]), "+f"(d[73]), "+f"(d[74]), "+f"(d[75]), "+f"(d[76]), "+f"(d[77]), "+f"(d[78]), "+f"(d[79])
      : "l"(da), "l"(db), "r"(scale_d), "n"(TA), "n"(TB));
  }
  static __device__ __forceinline__ void mma_first(float (&d)[80], uint64_t da, uint64_t db) {
    asm volatile("{\n.reg .pred p;\nsetp.ne.b32 p, 0, 0;\n"
      "wgmma.mma_async.sync.aligned.m64n160k16.f32.bf16.bf16 {%0, %1, %2, %3, %4, %5, %6, %7, %8, %9, %10, %11, %12, %13, %14, %15, %16, %17, %18, %19, %20, %21, %22, %23, %24, %25, %26, %27, %28, %29, %30, %31, %32, %33, %34, %35, %36, %37, %38, %39, %40, %41, %42, %43, %44, %45, %46, %47, %48, %49, %50, %51, %52, %53, %54, %55, %56, %57, %58, %59, %60, %61, %62, %63, %64, %65, %66, %67, %68, %69, %70, %71, %72, %73, %74, %75, %76, %77, %78, %79}, %80, %81, p, 1, 1, %82, %83;\n}\n"
      : "=f"(d[0]), "=f"(d[1]), "=f"(d[2]), "=f"(d[3]), "=f"(d[4]), "=f"(d[5]), "=f"(d[6]), "=f"(d[7]), "=f"(d[8]), "=f"(d[9]), "=f"(d[10]), "=f"(d[11]), "=f"(d[12]), "=f"(d[13]), "=f"(d[14]), "=f"(d[15]), "=f"(d[16]), "=f"(d[17]), "=f"(d[18]), "=f"(d[19]), "=f"(d[20]), "=f"(d[21]), "=f"(d[22]), "=f"(d[23]), "=f"(d[24]), "=f"(d[25]), "=f"(d[26]), "=f"(d[27]), "=f"(d[28]), "=f"(d[29]), "=f"(d[30]), "=f"(d[31]), "=f"(d[32]), "=f"(d[33]), "=f"(d[34]), "=f"(d[35]), "=f"(d[36]), "=f"(d[37]), "=f"(d[38]), "=f"(d[39]), "=f"(d[40]), "=f"(d[41]), "=f"(d[42]), "=f"(d[43]), "=f"(d[44]), "=f"(d[45]), "=f"(d[46]), "=f"(d[47]), "=f"(d[48]), "=f"(d[49]), "=f"(d[50]), "=f"(d[51]), "=f"(d[52]), "=f"(d[53]), "=f"(d[54]), "=f"(d[55]), "=f"(d[56]), "=f"(d[57]), "=f"(d[58]), "=f"(d[59]), "=f"(d[60]), "=f"(d[61]), "=f"(d[62]), "=f"(d[63]), "=f"(d[64]), "=f"(d[65]), "=f"(d[66]), "=f"(d[67]), "=f"(d[68]), "=f"(d[69]), "=f"(d[70]), "=f"(d[71]), "=f"(d[72]), "=f"(d[73]), "=f"(d[74]), "=f"(d[75]), "=f"(d[76]), "=f"(d[77]), "=f"(d[78]), "=f"(d[79])
      : "l"(da), "l"(db), "n"(TA), "n"(TB));
  }
};
template<int TA, int TB> struct Wgmma<192, TA, TB> {
  static __device__ __forceinline__ void mma(float (&d)[96], uint64_t da, uint64_t db, int scale_d) {
    asm volatile("{\n.reg .pred p;\nsetp.ne.b32 p, %98, 0;\n"
      "wgmma.mma_async.sync.aligned.m64n192k16.f32.bf16.bf16 {%0, %1, %2, %3, %4, %5, %6, %7, %8, %9, %10, %11, %12, %13, %14, %15, %16, %17, %18, %19, %20, %21, %22, %23, %24, %25, %26, %27, %28, %29, %30, %31, %32, %33, %34, %35, %36, %37, %38, %39, %40, %41, %42, %43, %44, %45, %46, %47, %48, %49, %50, %51, %52, %53, %54, %55, %56, %57, %58, %59, %60, %61, %62, %63, %64, %65, %66, %67, %68, %69, %70, %71, %72, %73, %74, %75, %76, %77, %78, %79, %80, %81, %82, %83, %84, %85, %86, %87, %88, %89, %90, %91, %92, %93, %94, %95}, %96, %97, p, 1, 1, %99, %100;\n}\n"
      : "+f"(d[0]), "+f"(d[1]), "+f"(d[2]), "+f"(d[3]), "+f"(d[4]), "+f"(d[5]), "+f"(d[6]), "+f"(d[7]), "+f"(d[8]), "+f"(d[9]), "+f"(d[10]), "+f"(d[11]), "+f"(d[12]), "+f"(d[13]), "+f"(d[14]), "+f"(d[15]), "+f"(d[16]), "+f"(d[17]), "+f"(d[18]), "+f"(d[19]), "+f"(d[20]), "+f"(d[21]), "+f"(d[22]), "+f"(d[23]), "+f"(d[24]), "+f"(d[25]), "+f"(d[26]), "+f"(d[27]), "+f"(d[28]), "+f"(d[29]), "+f"(d[30]), "+f"(d[31]), "+f"(d[32]), "+f"(d[33]), "+f"(d[34]), "+f"(d[35]), "+f"(d[36]), "+f"(d[37]), "+f"(d[38]), "+f"(d[39]), "+f"(d[40]), "+f"(d[41]), "+f"(d[42]), "+f"(d[43]), "+f"(d[44]), "+f"(d[45]), "+f"(d[46]), "+f"(d[47]), "+f"(d[48]), "+f"(d[49]), "+f"(d[50]), "+f"(d[51]), "+f"(d[52]), "+f"(d[53]), "+f"(d[54]), "+f"(d[55]), "+f"(d[56]), "+f"(d[57]), "+f"(d[58]), "+f"(d[59]), "+f"(d[60]), "+f"(d[61]), "+f"(d[62]), "+f"(d[63]), "+f"(d[64]), "+f"(d[65]), "+f"(d[66]), "+f"(d[67]), "+f"(d[68]), "+f"(d[69]), "+f"(d[70]), "+f"(d[71]), "+f"(d[72]), "+f"(d[73]), "+f"(d[74]), "+f"(d[75]), "+f"(d[76]), "+f"(d[77]), "+f"(d[78]), "+f"(d[79]), "+f"(d[80]), "+f"(d[81]), "+f"(d[82]), "+f"(d[83]), "+f"(d[84]), "+f"(d[85]), "+f"(d[86]), "+f"(d[87]), "+f"(d[88]), "+f"(d[89]), "+f"(d[90]), "+f"(d[91]), "+f"(d[92]), "+f"(d[93]), "+f"(d[94]), "+f"(d[95])
      : "l"(da), "l"(db), "r"(scale_d), "n"(TA), "n"(TB));
  }
  static __device__ __forceinline__ void mma_first(float (&d)[96], uint64_t da, uint64_t db) {
    asm volatile("{\n.reg .pred p;\nsetp.ne.b32 p, 0, 0;\n"
      "wgmma.mma_async.sync.aligned.m64n192k16.f32.bf16.bf16 {%0, %1, %2, %3, %4, %5, %6, %7, %8, %9, %10, %11, %12, %13, %14, %15, %16, %17, %18, %19, %20, %21, %22, %23, %24, %25, %26, %27, %28, %29, %30, %31, %32, %33, %34, %35, %36, %37, %38, %39, %40, %41, %42, %43, %44, %45, %46, %47, %48, %49, %50, %51, %52, %53, %54, %55, %56, %57, %58, %59, %60, %61, %62, %63, %64, %65, %66, %67, %68, %69, %70, %71, %72, %73, %74, %75, %76, %77, %78, %79, %80, %81, %82, %83, %84, %85, %86, %87, %88, %89, %90, %91, %92, %93, %94, %95}, %96, %97, p, 1, 1, %98, %99;\n}\n"
      : "=f"(d[0]), "=f"(d[1]), "=f"(d[2]), "=f"(d[3]), "=f"(d[4]), "=f"(d[5]), "=f"(d[6]), "=f"(d[7]), "=f"(d[8]), "=f"(d[9]), "=f"(d[10]), "=f"(d[11]), "=f"(d[12]), "=f"(d[13]), "=f"(d[14]), "=f"(d[15]), "=f"(d[16]), "=f"(d[17]), "=f"(d[18]), "=f"(d[19]), "=f"(d[20]), "=f"(d[21]), "=f"(d[22]), "=f"(d[23]), "=f"(d[24]), "=f"(d[25]), "=f"(d[26]), "=f"(d[27]), "=f"(d[28]), "=f"(d[29]), "=f"(d[30]), "=f"(d[31]), "=f"(d[32]), "=f"(d[33]), "=f"(d[34]), "=f"(d[35]), "=f"(d[36]), "=f"(d[37]), "=f"(d[38]), "=f"(d[39]), "=f"(d[40]), "=f"(d[41]), "=f"(d[42]), "=f"(d[43]), "=f"(d[44]), "=f"(d[45]), "=f"(d[46]), "=f"(d[47]), "=f"(d[48]), "=f"(d[49]), "=f"(d[50]), "=f"(d[51]), "=f"(d[52]), "=f"(d[53]), "=f"(d[54]), "=f"(d[55]), "=f"(d[56]), "=f"(d[57]), "=f"(d[58]), "=f"(d[59]), "=f"(d[60]), "=f"(d[61]), "=f"(d[62]), "=f"(d[63]), "=f"(d[64]), "=f"(d[65]), "=f"(d[66]), "=f"(d[67]), "=f"(d[68]), "=f"(d[69]), "=f"(d[70]), "=f"(d[71]), "=f"(d[72]), "=f"(d[73]), "=f"(d[74]), "=f"(d[75]), "=f"(d[76]), "=f"(d[77]), "=f"(d[78]), "=f"(d[79]), "=f"(d[80]), "=f"(d[81]), "=f"(d[82]), "=f"(d[83]), "=f"(d[84]), "=f"(d[85]), "=f"(d[86]), "=f"(d[87]), "=f"(d[88]), "=f"(d[89]), "=f"(d[90]), "=f"(d[91]), "=f"(d[92]), "=f"(d[93]), "=f"(d[94]), "=f"(d[95])
      : "l"(da), "l"(db), "n"(TA), "n"(TB));
  }
};

__device__ __forceinline__ uint64_t make_desc(uint32_t addr, uint32_t lbo, uint32_t sbo, uint32_t swz) {
  return (uint64_t)((addr & 0x3FFFF) >> 4) | ((uint64_t)(lbo >> 4) << 16) | ((uint64_t)(sbo >> 4) << 32) | ((uint64_t)swz << 62);
}

enum { B_FULL = 0, B_EMPTY = STAGES, B_SFREE = 2 * STAGES, B_SFREE1, B_Z1RDY, B_TURN0, B_TURN1, B_TAB, B_OWN, B_OWN1, B_PREV, B_TAG, B_STORE, B_STORE1, B_XN, B_SFREE2, B_FULL2, B_EMPTY2 = B_FULL2 + 4, B_DEP = B_EMPTY2 + 4, B_COUNT = B_DEP + 8 };

template<int V> struct IC { static constexpr int value = V; };
struct Ctx {
  uint32_t base;
  int warp, lane;
  __device__ __forceinline__ uint32_t bar(int i) const { return base + BAR_OFF + 8 * i; }
  __device__ __forceinline__ uint32_t ext(int off) const { return base + EXT_OFF + off; }
  __device__ __forceinline__ unsigned tag() const { mbar_wait(bar(B_TAG), 0); return __float_as_uint(lds32(ext(X_TAG))); }
};

__device__ __forceinline__ void release_stage(const Ctx& c, int it) {
  if (c.lane < 2) mbar_arrive_cluster(c.bar(B_EMPTY + (it & (STAGES - 1))), c.lane);
}

template<int N, int TA, int TB, bool ZI, int OWN = 0, int NOWN = 0, int PASS = 1>
__device__ __forceinline__ void mainloop(const Ctx& c, float (&acc)[2][N / 2], int it0, int n, bool pend, uint32_t pass_bar) {
  wgmma_fence();
  #pragma unroll 1
  for (int k = 0; k < n; k++) {
    int it = it0 + k, s = it & (STAGES - 1);
    bool rel = k > 0 || pend;
    mbar_wait(c.bar(B_FULL + s), (it / STAGES) & 1);
    TSTAMP(64 + it);
    if (pass_bar && k == n - PASS && c.lane == 0 && c.warp == 0) mbar_arrive(pass_bar);
    uint32_t sa = c.base + s * STAGE_BYTES, sb = sa + A_BYTES, mstep = 512;
    if (OWN == 1 && k < NOWN) sb = c.base + SBUF_OFF + k * (192 * 128);
    if (OWN == 2 && k < NOWN) { sa = c.base + SBUF_OFF + k * 8192; mstep = 192 * 128 / 16; }
    uint64_t da = make_desc(sa, TA == 0 ? 16 : 8192, 1024, 1);
    uint64_t db = make_desc(sb, TB == 0 ? 16 : 8192, 1024, 1);
    wgmma_fence();
    #pragma unroll
    for (int kk = 0; kk < 4; kk++) {
      int sd = (ZI && k == 0 && kk == 0) ? 0 : 1;
      #pragma unroll
      for (int mb = 0; mb < 2; mb++)
        Wgmma<N, TA, TB>::mma(acc[mb], da + (uint64_t)(mb * mstep + (TA == 0 ? kk * 2 : kk * 128)), db + (uint64_t)(TB == 0 ? kk * 2 : kk * 128), sd);
    }
    wgmma_commit();
    wgmma_wait<1>();
    if (rel) release_stage(c, it - 1);
    if (OWN && k == NOWN && c.lane == 0) mbar_arrive(c.bar(B_OWN + OWN - 1));
  }
}
template<int N>
__device__ __forceinline__ void fence_acc(float (&acc)[2][N / 2]) {
  #pragma unroll
  for (int mb = 0; mb < 2; mb++)
    #pragma unroll
    for (int e = 0; e < N / 2; e++) asm volatile("" : "+f"(acc[mb][e]) :: "memory");
}
template<int N>
__device__ __forceinline__ void undef_acc(float (&acc)[2][N / 2]) {
  #pragma unroll
  for (int mb = 0; mb < 2; mb++)
    #pragma unroll
    for (int e = 0; e < N / 2; e++) asm volatile("" : "=f"(acc[mb][e]));
}
template<int N>
__device__ __forceinline__ void drain(const Ctx& c, float (&acc)[2][N / 2], int it_last) {
  wgmma_wait<0>();
  fence_acc<N>(acc);
  release_stage(c, it_last);
}
template<int N>
__device__ __forceinline__ void first_bias(const Ctx& c, float (&acc)[2][N / 2]) {
  mbar_wait(c.bar(B_TAB), 0);
  uint64_t da = make_desc(c.ext(X_A), 2048, 128, 0), db = make_desc(c.ext(X_ONES), 0, 0, 0);
  wgmma_fence();
  Wgmma<N, 0, 0>::mma_first(acc[0], da, db);
  Wgmma<N, 0, 0>::mma_first(acc[1], da + 64, db);
  wgmma_commit();
}

__device__ __forceinline__ uint32_t stage_t_addr(const Ctx& c) {
  int mi = c.lane >> 3, r = c.lane & 7;
  return c.base + SBUF_OFF + ((mi >> 1) * 8 + r) * 128 + (((2 * c.warp + (mi & 1)) ^ r) << 4);
}

__global__ void __cluster_dims__(2, 1, 1) __launch_bounds__(384, 1)
fused_kernel(const __grid_constant__ Maps maps, const __nv_bfloat16* __restrict__ x, const __nv_bfloat16* __restrict__ hre,
             const __nv_bfloat16* __restrict__ him, const __nv_bfloat16* __restrict__ win, const __nv_bfloat16* __restrict__ wout,
             const __nv_bfloat16* __restrict__ sre,
             const __nv_bfloat16* __restrict__ sim, const __nv_bfloat16* __restrict__ wsp, const __nv_bfloat16* __restrict__ bsp) {
  Ctx c;
  asm("mov.u32 %0, smem_raw;" : "=r"(c.base));
  if (threadIdx.x == 1023) smem_raw[0] = 0;
  const int wg = __shfl_sync(0xffffffffu, threadIdx.x >> 7, 0), tid = threadIdx.x & 127;
  c.warp = __shfl_sync(0xffffffffu, tid >> 5, 0); c.lane = tid & 31;
  const int cta = blockIdx.x, rank = cta & 1, pair = cta >> 1;
  const bool isG = pair & 1;
  const int q = pair >> 1, rb = q >> 1, ct = (q & 1) * 2 + rank;
  const int row0 = rb * 128;
  const uint32_t sbuf = c.base + SBUF_OFF;

  const int xrow = row0 + ((isG ? 4 : 0) + ct) * 16;
  const uint32_t xa = sbuf + (threadIdx.x >> 4) * 1280 + (threadIdx.x & 15) * 16;
  if (wg < 2) {
    #pragma unroll
    for (int i = 0; i < 5; i++) cp_async16(xa + i * 256, x + (size_t)(xrow + (threadIdx.x >> 4)) * DM + (threadIdx.x & 15) * 8 + i * 128);
  }
  if (threadIdx.x == 256) {
    #pragma unroll
    for (int s = 0; s < B_COUNT; s++)
      mbar_init(c.bar(s), (s >= B_EMPTY && s < B_EMPTY + STAGES) ? 8 : (s == B_Z1RDY || s == B_STORE || s == B_STORE1) ? 128 : s == B_TAB ? 32 : (s == B_OWN || s == B_OWN1) ? 4 : s == B_XN ? 256 : (s >= B_EMPTY2 && s < B_EMPTY2 + 4) ? 16 : s == B_SFREE2 ? 2 : 1);
    asm volatile("fence.mbarrier_init.release.cluster;" ::: "memory");
  } else if (threadIdx.x >= 288 && threadIdx.x < 288 + M_COUNT) {
    prefetch_tmap(&maps.m[threadIdx.x - 288]);
  }
  if (threadIdx.x == 0) { TSTAMP1(0); TSTAMP_G(30); }
  __syncwarp();
  cluster_arrive();

  if (wg == 2) {
    asm volatile("setmaxnreg.dec.sync.aligned.u32 40;");
    if (c.warp == 0) {
      if (c.lane == 0) TSTAMP1(43);
      int it = 0;
      auto wait_dep = [&](int d, int ts) {
        if (c.lane == 0) TSTAMP1(ts);
        mbar_wait(c.bar(B_DEP + d), 0);
        fence_async_global();
        if (c.lane == 0) TSTAMP1(ts + 1);
      };
      auto run = [&](auto mode_c, const CUtensorMap* ma, const CUtensorMap* mb, int ka, int kb, int ks, int skip, int k0, int n, int nb0, uint32_t bytes, int fl, int ts) {
        constexpr int MODE = decltype(mode_c)::value;
        #pragma unroll 1
        for (int k = k0; k < n; k++, it++) {
          const int s = it & (STAGES - 1), ko = (k + (k >= skip ? 1 : 0)) * ks;
          const uint32_t sa = c.base + s * STAGE_BYTES, fb = c.bar(B_FULL + s);
          mbar_wait(c.bar(B_EMPTY + s), ((it / STAGES) & 1) ^ 1);
          if (elect_one()) {
            mbar_expect_tx(fb, bytes);
            tma_load_mc(sa + rank * 8192, ma, fb, ka + ko, row0 + rank * 64);
            if (MODE == 1) {
              #pragma unroll
              for (int b = 0; b < 3; b++) tma_load(sa + A_BYTES + b * 8192, mb, fb, nb0 + b * 64, ko);
            }
          }
          if (MODE == 0) {
            if (k == 0 && fl >= 0) wait_dep(fl, ts);
            if (elect_one()) tma_load(sa + A_BYTES, mb, fb, kb + ko, nb0);
          }
          if (c.lane == 0) TSTAMP1(192 + it);
        }
      };
      constexpr uint32_t B160 = A_BYTES + 160 * 128, B192 = A_BYTES + 192 * 128;
      { const long long tw = clock64(); while (clock64() - tw < W_DELAY); }
      if (elect_one()) {
        #pragma unroll
        for (int s = 0; s < STAGES; s++) {
          const uint32_t sb = c.base + s * STAGE_BYTES + A_BYTES, fb = c.bar(B_FULL + s);
          mbar_expect_tx(fb, isG ? B192 : B160);
          if (isG) {
            #pragma unroll
            for (int b = 0; b < 3; b++) tma_load(sb + b * 8192, &maps.m[M_WIN], fb, FH + ct * 192 + b * 64, s * 64);
          } else tma_load(sb, &maps.m[M_HRE], fb, s * 64, ct * 160);
        }
      }
      cluster_wait();
      wait_dep(0, 38);
      if (elect_one()) {
        #pragma unroll
        for (int s = 0; s < STAGES; s++) tma_load_mc(c.base + s * STAGE_BYTES + rank * 8192, &maps.m[M_X], c.bar(B_FULL + s), s * 64, row0 + rank * 64);
      }
      it = STAGES;
      if (isG) {
        #pragma unroll 1
        for (int t = 0; t < 2; t++) run(IC<1>(), &maps.m[M_X], &maps.m[M_WIN], 0, 0, 64, 99, t ? 0 : STAGES, 10, (t ? 0 : FH) + ct * 192, B192, -1, 0);
        run(IC<2>(), &maps.m[M_WSP], &maps.m[M_WSP], row0, 0, 64, 99, 0, 2, 0, A_BYTES, -1, 0);
      }
      #pragma unroll 1
      for (int sg = 0; sg < (isG ? 3 : 2); sg++) {
        const CUtensorMap *ma, *mb; int ka = 0, kb = 0, ks = 64, skip = 99, n, nb0 = ct * 160, fl = -1; uint32_t bytes = B160;
        if (!isG) {
          ma = &maps.m[M_X]; mb = &maps.m[M_HRE + sg]; n = 10;
        } else if (sg < 2) {
          ma = &maps.m[M_WSP]; mb = &maps.m[M_Z2NT]; n = 15; ka = kb = sg * 64; ks = 128; skip = rb; nb0 = ct * 192; fl = 1 + sg; bytes = B192;
        } else {
          #pragma unroll 1
          for (int k = 0; k < 2; k++, it++) {
            const int s = it & (STAGES - 1);
            mbar_wait(c.bar(B_EMPTY + s), ((it / STAGES) & 1) ^ 1);
            if (elect_one()) {
              mbar_expect_tx(c.bar(B_FULL + s), 192 * 128);
              #pragma unroll
              for (int b = 0; b < 3; b++) tma_load(c.base + s * STAGE_BYTES + A_BYTES + b * 8192, &maps.m[M_XB], c.bar(B_FULL + s), ct * 160 + b * 64, row0 + k * 64);
            }
          }
          ma = &maps.m[M_SIM]; mb = &maps.m[M_ABT]; n = JSPLIT; ka = (32 - JSPLIT) * 64; kb = SEQ + ka; fl = 3;
        }
        run(IC<0>(), ma, mb, ka, kb, ks, skip, (!isG && sg == 0) ? STAGES : 0, n, nb0, bytes, fl, 22 + sg * 2 + (sg == 2 ? 20 : 0));
      }
      if (!isG) {
        const int half = rb & 1;
        #pragma unroll 1
        for (int k = 0; k < NY + YSOLO; k++) {
          const int s = k & 3, im = k >= 16;
          const int kc = (k >= NY ? k - 16 : im ? half * (NY - 16 + YSOLO) + k - 16 : half * 16 + k) * 64;
          const uint32_t sa = c.base + s * STAGE2_BYTES, fb = c.bar(B_FULL2 + s);
          if (k < 3) { if (k == 0) mbar_wait(c.bar(B_EMPTY), 0); mbar_wait(c.bar(B_EMPTY + k + 1), 0); }
          else if (k == 3) mbar_wait(c.bar(B_SFREE2), 0);
          else mbar_wait(c.bar(B_EMPTY2 + s), ((k >> 2) & 1) ^ 1);
          if (elect_one()) {
            mbar_expect_tx(fb, k < NY ? STAGE2_BYTES : B160);
            if (k < NY) tma_load_mc(sa + rank * 16384, &maps.m[M_SRE2 + im], fb, kc, (rb >> 1) * 256 + rank * 128);
            else tma_load_mc(sa + half * 16384 + rank * 8192, &maps.m[M_SIM], fb, kc, row0 + rank * 64);
          }
          if (k == 0 || k == 16) wait_dep(1 + im, 22 + im * 2);
          if (elect_one()) tma_load(sa + 32768, &maps.m[M_ABT], fb, im * SEQ + kc, ct * 160);
          if (c.lane == 0) TSTAMP1(192 + 20 + k);
        }
      }
      if (isG) {
        #pragma unroll 1
        for (int k = 0; k < 12; k++, it++) {
          const int s = it & (STAGES - 1);
          const int f0 = k < 6 ? (ct ^ (k >= 3 ? 1 : 0)) * 192 + (k % 3) * 64 : ((ct >> 1) ^ 1) * 384 + (k - 6) * 64;
          const uint32_t sa = c.base + s * STAGE_BYTES, fb = c.bar(B_FULL + s);
          mbar_wait(c.bar(B_EMPTY + s), ((it / STAGES) & 1) ^ 1);
          if (elect_one()) {
            mbar_expect_tx(fb, k < 3 ? 192 * 128 : B192);
            #pragma unroll
            for (int b = 0; b < 3; b++) tma_load(sa + A_BYTES + b * 8192, &maps.m[M_WOUT], fb, ct * 160 + b * 64, f0);
          }
          if (k == 3) wait_dep(4, 26);
          if (k == 6) wait_dep(5, 44);
          if (k >= 3 && elect_one()) {
            if (k < 6) { tma_load(sa, &maps.m[M_HTLD], fb, row0, f0); tma_load(sa + 8192, &maps.m[M_HTLD], fb, row0 + 64, f0); }
            else tma_load_mc(sa + rank * 8192, &maps.m[M_HTLD], fb, row0 + rank * 64, f0);
          }
        }
        mbar_wait(c.bar(B_EMPTY + (IT_Y & 3)), ((IT_Y / STAGES) & 1) ^ 1);
        wait_dep(7, 28);
        if (elect_one()) {
          mbar_expect_tx(c.bar(B_FULL + (IT_Y & 3)), STAGE_BYTES);
          bulk_load(c.base + (IT_Y & 3) * STAGE_BYTES, g_y + (size_t)(64 + rb * 4 + ct) * 2560, STAGE_BYTES, c.bar(B_FULL + (IT_Y & 3)));
        }
      }
    } else {
      const int ht = tid - 32;
      unsigned tk = 0;
      if (ht == 0) tk = atomicAdd(&g_ticket, 1u);
      if (c.warp == 2) {
        #pragma unroll
        for (int j = 0; j < 4; j++) {
          const int i = c.lane + j * 32;
          sts128u(c.ext(X_A) + i * 16, pack_bf16(0.5f * __bfloat162float(bsp[row0 + i]), 0.f), 0, 0, 0, 1);
          sts128u(c.ext(X_Z) + i * 16, 0, 0, 0, 0, 1);
        }
        sts128u(c.ext(X_ONES) + (ht & 7) * 16, 0x00003F80u, 0, 0, 0, ht < 40);
        #pragma unroll 1
        for (int i = c.lane; i < 512; i += 32) {
          const int r = i >> 3, ch = (i & 7) ^ (r & 7), e = ch == (r >> 3) ? (r & 7) : 8;
          const uint32_t one = (e & 1) ? 0x3F800000u : 0x00003F80u;
          sts128u(c.ext(X_ID) + i * 16, (e >> 1) == 0 ? one : 0, (e >> 1) == 1 ? one : 0, (e >> 1) == 2 ? one : 0, (e >> 1) == 3 ? one : 0, 1);
        }
        fence_async_smem();
      }
      cluster_wait();
      if (ht == 0) { sts32(c.ext(X_TAG), __uint_as_float((tk >> 7) + 1u)); mbar_arrive(c.bar(B_TAG)); }
      if (c.warp == 2) mbar_arrive(c.bar(B_TAB));
      __syncwarp();
      const unsigned tag = c.tag();
      if (c.warp == 1) {
        mbar_wait(c.bar(B_XN), 0);
        if (c.lane == 0) TSTAMP1(33);
        if (elect_one()) {
          bulk_store(g_xn + (size_t)xrow * DM, sbuf, 16 * 1280);
          bulk_commit();
          bulk_wait_all();
          flag_set(FL_XN + rb * 8 + (isG ? 4 : 0) + ct, tag, 1);
        }
        if (c.lane == 0) TSTAMP1(35);
      }
      __syncwarp();
      if (c.warp == 3) {
        #pragma unroll 1
        for (int d = 0; d < (isG ? 8 : 3); d++) {
          const int fl = d == 0 ? FL_XN + rb * 8 + rank * 4 : !isG ? FL_AB + ((d - 1) * 4 + ct) * 16 : d < 3 ? FL_Z2N + (ct * 2 + d - 1) * 16
                         : d == 3 ? FL_AB + (4 + ct) * 16 : d == 4 ? FL_H + rb * 4 + (ct ^ 1) : d == 5 ? FL_H + rb * 4 + ((ct >> 1) ^ 1) * 2 : FL_F + (rb * 4 + ct) * 2 + d - 6;
          const int nfl = d == 0 ? 4 : d < 4 ? 16 : d == 5 ? 2 : 1;
          #pragma unroll 1
          for (int sp = 0; sp < SPIN_MAX; sp++) {
            const bool ok = flag_get(fl + (c.lane & (nfl - 1))) == tag;
            if (__all_sync(0xffffffffu, ok)) break;
            FLAG_SLEEP;
          }
          if (c.lane == 0) mbar_arrive(c.bar(B_DEP + d));
          if (d == 6) {
            if (c.lane == 0) TSTAMP1(60);
            mbar_wait(c.bar(B_SFREE1), 0); mbar_wait(c.bar(B_OWN1), 0);
            fence_async_global();
            if (elect_one()) {
              mbar_expect_tx(c.bar(B_PREV), STAGE_BYTES);
              bulk_load(sbuf, g_y + (size_t)(rb * 4 + ct) * 2560, STAGE_BYTES, c.bar(B_PREV));
            }
            __syncwarp();
          }
        }
      }
      if (c.warp == 2) {
        const long long t0 = clock64();
        while (clock64() - t0 < PF_W) __nanosleep(100);
        {
          const int ln = cta * 32 + c.lane;
          #pragma unroll 1
          for (int i = ln; i < 6400; i += 4096) { prefetch_l2(hre + (size_t)i * 64); prefetch_l2(him + (size_t)i * 64); }
          #pragma unroll 1
          for (int i = ln; i < 15360; i += 4096) prefetch_l2(win + (size_t)i * 64);
          #pragma unroll 1
          for (int i = ln; i < 7680; i += 4096) prefetch_l2(wout + (size_t)i * 64);
        }
        const size_t off = (size_t)(row0 + ct * 32 + c.lane) * SEQ;
        #pragma unroll 1
        for (int u = 0; u < (PF_STEP ? (isG ? 16 : 32) : 0); u++) {
          while (clock64() - t0 < (isG ? PF_START_G + u * PF_STEP_G : PF_START + u * PF_STEP)) __nanosleep(100);
          const int blk = isG ? u : (u & 1) * 8 + ((u & 15) >> 1);
          const __nv_bfloat16* pm = (isG ? wsp : u < 16 ? sre : sim) + off + blk * 128;
          prefetch_l2(pm); prefetch_l2(pm + 64);
        }
        if (isG) {
          #pragma unroll 1
          for (int i = 0; i < 10; i++) {
            while (clock64() - t0 < PF_X + i * 1000) __nanosleep(100);
            prefetch_l2(x + (size_t)(row0 + ct * 32 + c.lane) * DM + i * 64);
          }
        }
      }
      if (c.warp == 1) {
        #pragma unroll 1
        for (int job = 0; job < (isG ? 5 : 4); job++) {
          mbar_wait(c.bar(B_STORE + (job & 1)), (job >> 1) & 1);
          if (c.lane == 0) TSTAMP1(48 + job * 2 + (job == 4 ? 2 : 0));
          if (elect_one()) {
            if (isG && job >= 3) {
              #pragma unroll
              for (int b = 0; b < 5; b++) tma_store(&maps.m[M_OUT], c.base + ((IT_Y + 1) & 3) * STAGE_BYTES + b * 8192 + (job - 3) * 4096, ct * 160 + b * 32, row0 + (job - 3) * 64, 1);
              bulk_commit();
              if (job == 4) bulk_wait_read();
            } else if (!isG && job >= 2) {
              const int w = (rb & 1) ^ (job == 2 ? 1 : 0), rbo = (rb & ~1) + w;
              #pragma unroll
              for (int i = 0; i < 3; i++)
                bulk_store(g_y + (size_t)((job - 2) * 64 + rbo * 4 + ct) * 2560 + i * 1024, c.base + i * STAGE2_BYTES + w * 16384, i < 2 ? 16384 : 8192);
              bulk_commit();
              bulk_wait_all();
              flag_set(FL_F + (rbo * 4 + ct) * 2 + job - 2, tag, 1);
            } else {
              const CUtensorMap* tm = &maps.m[isG ? (job == 2 ? M_HT : M_Z2NTS) : M_ABTS];
              const int c0 = row0 + (isG ? 0 : job * SEQ), rows = (isG ? 192 : 160) / ST_SPLIT, c1 = ct * rows * ST_SPLIT;
              const int p0 = isG && job == 1 ? ST_SPLIT : 0, p1 = isG && job == 0 ? ST_SPLIT : 2 * ST_SPLIT;
              #pragma unroll 1
              for (int p = p0; p < p1; p++) {
                tma_store(tm, sbuf + p * rows * 128, c0 + (p / ST_SPLIT) * 64, c1 + (p % ST_SPLIT) * rows, 1);
                bulk_commit();
                if (ST_SPLIT > 1) { const long long tg = clock64(); while (clock64() - tg < (isG ? ST_GAP_G : ST_GAP_F)); }
              }
              bulk_wait_all();
              flag_set(isG ? (job == 2 ? FL_H + rb * 4 + ct : FL_Z2N + (ct * 2 + job) * 16 + rb) : FL_AB + (job * 4 + ct) * 16 + rb, tag, 1);
              if (!(isG && job == 0)) mbar_arrive(c.bar(B_SFREE + job - (isG ? 1 : 0)));
              if (!isG && job == 1) { mbar_arrive_cluster(c.bar(B_SFREE2), 0); mbar_arrive_cluster(c.bar(B_SFREE2), 1); }
            }
          }
          __syncwarp();
          if (c.lane == 0) TSTAMP1(49 + job * 2 + (job == 4 ? 2 : 0));
        }
      }
    }
  } else {
    asm volatile("setmaxnreg.inc.sync.aligned.u32 232;");
    const uint32_t a0 = stage_t_addr(c);
    #pragma unroll 1
    for (int live = 0; live < 2; live++) {
      if (live) cp_async_wait();
      float v[40], sm = 0.f, sq = 0.f;
      #pragma unroll
      for (int i = 0; i < 5; i++) {
        const uint4 u = lds128u(xa + i * 256);
        v[8 * i] = bf_lo(u.x); v[8 * i + 1] = bf_hi(u.x); v[8 * i + 2] = bf_lo(u.y); v[8 * i + 3] = bf_hi(u.y);
        v[8 * i + 4] = bf_lo(u.z); v[8 * i + 5] = bf_hi(u.z); v[8 * i + 6] = bf_lo(u.w); v[8 * i + 7] = bf_hi(u.w);
      }
      #pragma unroll
      for (int i = 0; i < 40; i += 4) sm += (v[i] + v[i + 1]) + (v[i + 2] + v[i + 3]);
      #pragma unroll
      for (int o = 1; o < 16; o <<= 1) sm += __shfl_xor_sync(0xffffffffu, sm, o);
      const float mean = sm * (1.0f / DM);
      #pragma unroll
      for (int i = 0; i < 40; i += 2) { v[i] -= mean; v[i + 1] -= mean; sq += fmaf(v[i], v[i], v[i + 1] * v[i + 1]); }
      #pragma unroll
      for (int o = 1; o < 16; o <<= 1) sq += __shfl_xor_sync(0xffffffffu, sq, o);
      const float rstd = rsqrtf(sq * (1.0f / DM) + LN_EPS);
      #pragma unroll
      for (int i = 0; i < 5; i++)
        sts128u(xa + i * 256, pack_bf16(v[8 * i] * rstd, v[8 * i + 1] * rstd), pack_bf16(v[8 * i + 2] * rstd, v[8 * i + 3] * rstd),
                pack_bf16(v[8 * i + 4] * rstd, v[8 * i + 5] * rstd), pack_bf16(v[8 * i + 6] * rstd, v[8 * i + 7] * rstd), live);
      fence_async_smem();
      if (!live) cluster_wait();
      mbar_arrive_if(c.bar(B_XN), live);
    }
    auto staged = [&](int job, int live) { fence_async_smem(); mbar_arrive_if(c.bar(B_STORE + (job & 1)), live); };

    const int orow = c.warp * 16 + ((c.lane >> 3) & 1) * 8 + (c.lane & 7);
    const uint32_t o0 = orow * 64 + (((c.lane >> 4) ^ ((orow >> 1) & 3)) << 4);
    float acc[2][80];
    if (!isG) {
      auto epi_ab = [&](int job, uint32_t sgn, int live) {
        #pragma unroll
        for (int mb = 0; mb < 2; mb++) {
          if (live || c.warp == mb) {
            #pragma unroll
            for (int j = 0; j < 20; j += 2)
              stmatrix_x4_t(a0 + mb * (160 * 128) + j * 1024,
                            pack_bf16(acc[mb][4 * j + 0], acc[mb][4 * j + 1]) ^ sgn, pack_bf16(acc[mb][4 * j + 2], acc[mb][4 * j + 3]) ^ sgn,
                            pack_bf16(acc[mb][4 * j + 4], acc[mb][4 * j + 5]) ^ sgn, pack_bf16(acc[mb][4 * j + 6], acc[mb][4 * j + 7]) ^ sgn, live);
          }
        }
        staged(job, live);
      };
      if (wg == 0) {
        mainloop<160, 0, 0, true>(c, acc, 0, 10, false, c.bar(B_TURN1));
        drain<160>(c, acc, 9);
        TSTAMP(4);
      }
      epi_ab(0, 0u, wg == 0);
      if (wg == 1) {
        TSTAMP(36);
        mbar_wait(c.bar(B_TURN1), 0);
        mainloop<160, 0, 0, true>(c, acc, 10, 10, false, 0);
        drain<160>(c, acc, 19);
        TSTAMP(8);
        mbar_wait(c.bar(B_SFREE), 0);
        epi_ab(1, 0x80008000u, 1);
      }
      TSTAMP(12 + wg * 45);
      wgmma_fence();
      #pragma unroll 1
      for (int k = 0; k < (wg == (rb & 1) ? NY + YSOLO : NY); k++) {
        const int s = k & 3;
        mbar_wait(c.bar(B_FULL2 + s), (k >> 2) & 1);
        if (wg == (rb & 1)) TSTAMP(84 + k);
        const uint32_t sa = c.base + s * STAGE2_BYTES;
        const uint64_t da = make_desc(sa + wg * 16384, 16, 1024, 1), db = make_desc(sa + 32768, 16, 1024, 1);
        wgmma_fence();
        #pragma unroll
        for (int kk = 0; kk < 4; kk++)
          #pragma unroll
          for (int mb = 0; mb < 2; mb++) Wgmma<160, 0, 0>::mma(acc[mb], da + (uint64_t)(mb * 512 + kk * 2), db + (uint64_t)(kk * 2), (k | kk) ? 1 : 0);
        wgmma_commit();
        if (k > 0) { wgmma_wait<1>(); if (c.lane < (k > NY ? 4 : 2)) mbar_arrive_cluster(c.bar(B_EMPTY2 + ((k - 1) & 3)), c.lane & 1); }
      }
      wgmma_wait<0>();
      fence_acc<160>(acc);
      if (wg != (rb & 1) && c.lane < 2) mbar_arrive_cluster(c.bar(B_EMPTY2 + ((NY - 1) & 3)), c.lane);
      if (wg == (rb & 1)) TSTAMP(13);
      named_sync(1 + wg, 128);
      #pragma unroll
      for (int i = 0; i < 20; i++) {
        const float* a = &acc[i / 10][(i % 10) * 8];
        sts128u(c.base + (i >> 3) * STAGE2_BYTES + wg * 16384 + (i & 7) * 2048 + tid * 16, pack_bf16(a[0], a[1]), pack_bf16(a[2], a[3]), pack_bf16(a[4], a[5]), pack_bf16(a[6], a[7]), 1);
      }
      staged(wg == (rb & 1) ? 3 : 2, 1);
    } else {
      float acz[2][96];
      if (wg == 0) {
        mainloop<192, 0, 1, true>(c, acz, 0, 10, false, TURN_AT == 0 ? c.bar(B_TURN1) : 0);
        drain<192>(c, acz, 9);
        TSTAMP(4);
      }
      {
        const int live = wg == 0;
        const unsigned tag = c.tag();
        u64* const zst = &g_z2stat[(row0 + c.warp * 16 + (c.lane >> 2)) * 2];
        float s0 = 0.f, s1 = 0.f, q0 = 0.f, q1 = 0.f;
        auto gelu_part = [&](auto mb_c, auto hf_c) {
          constexpr int mb = decltype(mb_c)::value, hf = decltype(hf_c)::value;
          if (live || c.warp == mb * 2 + hf) {
            #pragma unroll
            for (int j = hf * 12; j < hf * 12 + 12; j++) {
              const float g0 = gelu2(acz[mb][4 * j]), g1 = gelu2(acz[mb][4 * j + 1]);
              const float g2 = gelu2(acz[mb][4 * j + 2]), g3 = gelu2(acz[mb][4 * j + 3]);
              acz[mb][4 * j] = g0; acz[mb][4 * j + 1] = g1; acz[mb][4 * j + 2] = g2; acz[mb][4 * j + 3] = g3;
              s0 += g0 + g1; s1 += g2 + g3;
              q0 = fmaf(g0, g0, q0); q0 = fmaf(g1, g1, q0); q1 = fmaf(g2, g2, q1); q1 = fmaf(g3, g3, q1);
            }
          }
        };
        auto publish = [&](int mb) {
          const bool up = c.lane & 2;
          float sm = (up ? s1 : s0) + __shfl_xor_sync(0xffffffffu, up ? s0 : s1, 2);
          float sq = (up ? q1 : q0) + __shfl_xor_sync(0xffffffffu, up ? q0 : q1, 2);
          sm += __shfl_xor_sync(0xffffffffu, sm, 1); sq += __shfl_xor_sync(0xffffffffu, sq, 1);
          st_tag2(zst + (mb * 64 + (up ? 8 : 0)) * 2 + ct * (SEQ * 2), tagged(sm, tag), tagged(sq, tag), live && !(c.lane & 1));
          s0 = s1 = q0 = q1 = 0.f;
          if (live) TSTAMP(5 + mb * 11);
        };
        uint4 e0 = make_uint4(0, 0, 0, 0), e1 = e0;
        auto fetch = [&](int mb) {
          e0 = ld_tag2(zst + mb * 128 + (c.lane & 3) * (SEQ * 2), live); e1 = ld_tag2(zst + mb * 128 + 16 + (c.lane & 3) * (SEQ * 2), live);
        };
        auto norm_stage = [&](auto mb_c) {
          constexpr int mb = decltype(mb_c)::value;
          if (live || c.warp == mb * 2) {
            #pragma unroll 1
            for (int sp = 0; sp < SPIN_MAX; sp++) {
              const bool ok = e0.y == tag && e0.w == tag && e1.y == tag && e1.w == tag;
              if (__all_sync(0xffffffffu, ok) || !live) break;
              fetch(mb);
            }
            float m0 = __uint_as_float(e0.x), v0 = __uint_as_float(e0.z), m1 = __uint_as_float(e1.x), v1 = __uint_as_float(e1.z);
            #pragma unroll
            for (int o = 1; o < 4; o <<= 1) {
              m0 += __shfl_xor_sync(0xffffffffu, m0, o); v0 += __shfl_xor_sync(0xffffffffu, v0, o);
              m1 += __shfl_xor_sync(0xffffffffu, m1, o); v1 += __shfl_xor_sync(0xffffffffu, v1, o);
            }
            m0 *= 1.0f / FH; m1 *= 1.0f / FH;
            const float r0 = 0.5f * rsqrtf(fmaxf(v0 * (1.0f / FH) - m0 * m0, 0.f) + 4.0f * LN_EPS), r1 = 0.5f * rsqrtf(fmaxf(v1 * (1.0f / FH) - m1 * m1, 0.f) + 4.0f * LN_EPS);
            const float n0 = -m0 * r0, n1 = -m1 * r1;
            if (live && mb == 0) TSTAMP(17);
            #pragma unroll
            for (int j = 0; j < 24; j += 2) {
              if (mb == 0 && j == 12) fetch(1);
              stmatrix_x4_t(a0 + mb * (192 * 128) + j * 1024,
                            pack_bf16(fmaf(acz[mb][4 * j + 0], r0, n0), fmaf(acz[mb][4 * j + 1], r0, n0)), pack_bf16(fmaf(acz[mb][4 * j + 2], r1, n1), fmaf(acz[mb][4 * j + 3], r1, n1)),
                            pack_bf16(fmaf(acz[mb][4 * j + 4], r0, n0), fmaf(acz[mb][4 * j + 5], r0, n0)), pack_bf16(fmaf(acz[mb][4 * j + 6], r1, n1), fmaf(acz[mb][4 * j + 7], r1, n1)), live);
            }
            staged(mb, live);
          }
        };
        gelu_part(IC<0>(), IC<0>());
        if (TURN_AT == 4 && threadIdx.x == 0) mbar_arrive(c.bar(B_TURN1));
        gelu_part(IC<0>(), IC<1>());
        publish(0);
        if (TURN_AT == 1 && threadIdx.x == 0) mbar_arrive(c.bar(B_TURN1));
        gelu_part(IC<1>(), IC<0>());
        fetch(0);
        if (TURN_AT == 3 && threadIdx.x == 0) mbar_arrive(c.bar(B_TURN1));
        gelu_part(IC<1>(), IC<1>());
        publish(1);
        if (TURN_AT == 2 && threadIdx.x == 0) mbar_arrive(c.bar(B_TURN1));
        norm_stage(IC<0>());
        norm_stage(IC<1>());
      }
      if (wg == 1) {
        TSTAMP(36);
        mbar_wait(c.bar(B_TURN1), 0);
        mainloop<192, 0, 1, true>(c, acz, 10, 10, false, c.bar(B_TURN0));
        drain<192>(c, acz, 19);
        TSTAMP(8);
        mbar_wait(c.bar(B_SFREE), 0);
        mbar_wait(c.bar(B_OWN), 0);
        #pragma unroll
        for (int mb = 0; mb < 2; mb++)
          #pragma unroll
          for (int j = 0; j < 24; j += 2)
            stmatrix_x4_t(a0 + mb * (192 * 128) + j * 1024,
                          pack_bf16(acz[mb][4 * j + 0], acz[mb][4 * j + 1]), pack_bf16(acz[mb][4 * j + 2], acz[mb][4 * j + 3]),
                          pack_bf16(acz[mb][4 * j + 4], acz[mb][4 * j + 5]), pack_bf16(acz[mb][4 * j + 6], acz[mb][4 * j + 7]), 1);
      } else {
        mbar_wait(c.bar(B_STORE), 0); mbar_wait(c.bar(B_STORE1), 0);
        mbar_wait(c.bar(B_TURN0), 0);
        TSTAMP(12);
        first_bias<192>(c, acz);
        mainloop<192, 0, 0, false, 1, 2>(c, acz, 20, 32, false, c.bar(B_TURN1));
        drain<192>(c, acz, 51);
        TSTAMP(13);
        mbar_wait(c.bar(B_Z1RDY), 0);
      }
      if (wg == 0 || c.warp == 0) {
        const int live = wg == 0;
        uint32_t gp[24][4], z[24][4];
        #pragma unroll
        for (int i = 0; i < 24; i++)
          #pragma unroll
          for (int e = 0; e < 4; e++) gp[i][e] = pack_bf16(acz[i / 12][(i % 12) * 8 + 2 * e], acz[i / 12][(i % 12) * 8 + 2 * e + 1]);
        #pragma unroll
        for (int i = 0; i < 24; i++) ldmatrix_x4_t(a0 + i * 2048, z[i], 1);
        #pragma unroll
        for (int i = 0; i < 24; i++)
          stmatrix_x4_t(a0 + i * 2048, mul_bf16x2(z[i][0], gp[i][0]), mul_bf16x2(z[i][1], gp[i][1]), mul_bf16x2(z[i][2], gp[i][2]), mul_bf16x2(z[i][3], gp[i][3]), live);
        staged(2, live);
      }
      if (wg == 1) {
        named_sync(2, 128);
        #pragma unroll 1
        for (int i = 0; i < 24; i += 3) {
          uint4 v3[3];
          #pragma unroll
          for (int k = 0; k < 3; k++) v3[k] = lds128u(sbuf + tid * 16 + (i + k) * 2048);
          #pragma unroll
          for (int k = 0; k < 3; k++) {
            uint32_t w[4] = {v3[k].x, v3[k].y, v3[k].z, v3[k].w};
            #pragma unroll
            for (int e = 0; e < 4; e++) w[e] = pack_bf16(gelu2(bf_lo(w[e])), gelu2(bf_hi(w[e])));
            sts128u(sbuf + tid * 16 + (i + k) * 2048, w[0], w[1], w[2], w[3], 1);
          }
        }
        mbar_arrive(c.bar(B_Z1RDY));
        TSTAMP(11);
        mbar_wait(c.bar(B_TURN1), 1);
        mbar_wait(c.bar(B_TAB), 0);
        #pragma unroll
        for (int mb = 0; mb < 2; mb++) {
          const int it = 52 + mb, s = it & (STAGES - 1);
          mbar_wait(c.bar(B_FULL + s), (it / STAGES) & 1);
          TSTAMP(64 + it);
          const uint64_t da = make_desc(c.ext(X_ID), 16, 1024, 1), db = make_desc(c.base + s * STAGE_BYTES + A_BYTES, 8192, 1024, 1);
          wgmma_fence();
          Wgmma<160, 0, 1>::mma_first(acc[mb], da, db);
          #pragma unroll
          for (int kk = 1; kk < 4; kk++) Wgmma<160, 0, 1>::mma(acc[mb], da + (uint64_t)(kk * 2), db + (uint64_t)(kk * 128), 1);
          wgmma_commit();
          if (mb) { wgmma_wait<1>(); release_stage(c, 52); }
        }
        mainloop<160, 0, 0, false>(c, acc, IT_F, JSPLIT, true, 0);
        TSTAMP(15);
        mbar_wait(c.bar(B_STORE), 1);
        mainloop<160, 1, 1, false, 2, 3>(c, acc, IT_F + JSPLIT, 12, true, 0);
        drain<160>(c, acc, IT_Y - 1);
        TSTAMP(9);
        named_sync(2, 128);
        mbar_wait(c.bar(B_PREV), 0);
        mbar_wait(c.bar(B_FULL + (IT_Y & 3)), (IT_Y / STAGES) & 1);
        TSTAMP(56);
      }
      if (wg == 1 || c.warp == 0) {
        const int live = wg == 1;
        const uint32_t y1 = c.base + (IT_Y & 3) * STAGE_BYTES + tid * 16, ob = c.base + ((IT_Y + 1) & 3) * STAGE_BYTES + o0;
        #pragma unroll
        for (int g = 0; g < 4; g++) {
          uint4 u[5], v[5];
          #pragma unroll
          for (int i = 0; i < 5; i++) { u[i] = lds128u(sbuf + tid * 16 + (g * 5 + i) * 2048); v[i] = lds128u(y1 + (g * 5 + i) * 2048); }
          #pragma unroll
          for (int i = 0; i < 5; i++) {
            const int j = (g & 1) * 5 + i;
            const float* a = &acc[g >> 1][j * 8];
            stmatrix_x4((ob ^ ((j & 1) << 5)) + (j >> 1) * 8192 + (g >> 1) * 4096,
                        add_bf16x2(add_bf16x2(u[i].x, v[i].x), pack_bf16(a[0], a[1])), add_bf16x2(add_bf16x2(u[i].y, v[i].y), pack_bf16(a[2], a[3])),
                        add_bf16x2(add_bf16x2(u[i].z, v[i].z), pack_bf16(a[4], a[5])), add_bf16x2(add_bf16x2(u[i].w, v[i].w), pack_bf16(a[6], a[7])), live);
          }
          if (g & 1) staged(3 + (g >> 1), live);
        }
      }
    }
  }
  __syncwarp();
  cluster_arrive();
  cluster_wait();
  if (threadIdx.x == 0) { TSTAMP1(21); TSTAMP_G(31); }
}

typedef CUresult (*EncodeFn)(CUtensorMap*, CUtensorMapDataType, cuuint32_t, void*, const cuuint64_t*, const cuuint64_t*,
                             const cuuint32_t*, const cuuint32_t*, CUtensorMapInterleave, CUtensorMapSwizzle,
                             CUtensorMapL2promotion, CUtensorMapFloatOOBfill);

void make_map(EncodeFn enc, CUtensorMap* m, const void* p, int rows, int cols, int box_rows, int box_cols, CUtensorMapSwizzle sw) {
  cuuint64_t gd[2] = {(cuuint64_t)cols, (cuuint64_t)rows};
  cuuint64_t gs[1] = {(cuuint64_t)cols * 2};
  cuuint32_t bd[2] = {(cuuint32_t)box_cols, (cuuint32_t)box_rows};
  cuuint32_t es[2] = {1, 1};
  enc(m, CU_TENSOR_MAP_DATA_TYPE_BFLOAT16, 2, (void*)p, gd, gs, bd, es, CU_TENSOR_MAP_INTERLEAVE_NONE, sw,
      CU_TENSOR_MAP_L2_PROMOTION_L2_256B, CU_TENSOR_MAP_FLOAT_OOB_FILL_NONE);
}

}

extern "C" void kernel_launch(void* const* d_in, const int* in_sizes, int n_in, void* d_out, int out_size) {
  const __nv_bfloat16* x = (const __nv_bfloat16*)d_in[0];
  const __nv_bfloat16* sre = (const __nv_bfloat16*)d_in[1];
  const __nv_bfloat16* sim = (const __nv_bfloat16*)d_in[2];
  const __nv_bfloat16* hre = (const __nv_bfloat16*)d_in[3];
  const __nv_bfloat16* him = (const __nv_bfloat16*)d_in[4];
  const __nv_bfloat16* win = (const __nv_bfloat16*)d_in[6];
  const __nv_bfloat16* wsp = (const __nv_bfloat16*)d_in[7];
  const __nv_bfloat16* bsp = (const __nv_bfloat16*)d_in[8];
  const __nv_bfloat16* wout = (const __nv_bfloat16*)d_in[9];

  void* fn = nullptr;
  cudaDriverEntryPointQueryResult qr;
  cudaGetDriverEntryPoint("cuTensorMapEncodeTiled", &fn, cudaEnableDefault, &qr);
  EncodeFn enc = (EncodeFn)fn;
  void *p_xn, *p_abT, *p_z2nT, *p_hT;
  cudaGetSymbolAddress(&p_xn, g_xn);
  cudaGetSymbolAddress(&p_abT, g_abT);
  cudaGetSymbolAddress(&p_z2nT, g_z2nT);
  cudaGetSymbolAddress(&p_hT, g_hT);
  Maps m;
  const CUtensorMapSwizzle S128 = CU_TENSOR_MAP_SWIZZLE_128B;
  make_map(enc, &m.m[M_X], p_xn, SEQ, DM, 64, 64, S128);
  make_map(enc, &m.m[M_HRE], hre, DM, DM, 160, 64, S128);
  make_map(enc, &m.m[M_HIM], him, DM, DM, 160, 64, S128);
  make_map(enc, &m.m[M_WIN], win, DM, 2 * FH, 64, 64, S128);
  make_map(enc, &m.m[M_SRE2], sre, SEQ, SEQ, 128, 64, S128);
  make_map(enc, &m.m[M_SIM2], sim, SEQ, SEQ, 128, 64, S128);
  make_map(enc, &m.m[M_SIM], sim, SEQ, SEQ, 64, 64, S128);
  make_map(enc, &m.m[M_WSP], wsp, SEQ, SEQ, 64, 64, S128);
  make_map(enc, &m.m[M_ABT], p_abT, DM, 2 * SEQ, 160, 64, S128);
  make_map(enc, &m.m[M_Z2NT], p_z2nT, FH, SEQ, 192, 64, S128);
  make_map(enc, &m.m[M_HT], p_hT, FH, SEQ, 192 / ST_SPLIT, 64, S128);
  make_map(enc, &m.m[M_HTLD], p_hT, FH, SEQ, 64, 64, S128);
  make_map(enc, &m.m[M_WOUT], wout, FH, DM, 64, 64, S128);
  make_map(enc, &m.m[M_ABTS], p_abT, DM, 2 * SEQ, 160 / ST_SPLIT, 64, S128);
  make_map(enc, &m.m[M_Z2NTS], p_z2nT, FH, SEQ, 192 / ST_SPLIT, 64, S128);
  make_map(enc, &m.m[M_OUT], d_out, SEQ, DM, 64, 32, CU_TENSOR_MAP_SWIZZLE_64B);
  make_map(enc, &m.m[M_XB], x, SEQ, DM, 64, 64, S128);
  cudaFuncSetAttribute(fused_kernel, cudaFuncAttributeMaxDynamicSharedMemorySize, SMEM_BYTES);
  fused_kernel<<<NCTA, 384, SMEM_BYTES>>>(m, x, hre, him, win, wout, sre, sim, wsp, bsp);
}
```

```cpp
#include <cuda.h>
#include <cuda_runtime.h>
#include <cuda_bf16.h>
#include <stdint.h>

extern __shared__ __align__(1024) uint8_t smem_raw[];

namespace {

constexpr int SEQ = 2048, DM = 640, FH = 768;
constexpr int STAGES = 4;
constexpr int STAGE_BYTES = 40960;
constexpr int A_BYTES = 16384;
constexpr int SBUF_OFF = STAGES * STAGE_BYTES;
constexpr int EXT_OFF = SBUF_OFF + 49152;
constexpr int X_ID = 0, X_A = 8192, X_Z = 10240, X_ONES = 12288, X_TAG = 12416, X_MASK = 12420;
constexpr int BAR_OFF = EXT_OFF + 12544;
constexpr int SMEM_BYTES = BAR_OFF + 512;
constexpr int JSPLIT = 4;
constexpr int YSOLO = 4;
static_assert((JSPLIT + YSOLO) % 2 == 0, "the two F-CTAs of a tile split K evenly");
constexpr int NY = 16 + (32 - JSPLIT - YSOLO) / 2;
constexpr int IT_F = 54;
constexpr int IT_Y = IT_F + JSPLIT + 12;
constexpr int STAGE2_BYTES = 32768 + 160 * 128;
constexpr int NCTA = 128;
constexpr float LN_EPS = 1e-5f;
static_assert(SMEM_BYTES <= 232448, "smem");

enum { M_X, M_HRE, M_HIM, M_WIN, M_SRE2, M_SIM2, M_SIM, M_WSP, M_ABT, M_Z2NT, M_HT, M_HTLD, M_WOUT, M_OUT, M_XB, M_COUNT };
struct Maps { CUtensorMap m[M_COUNT]; };

typedef unsigned long long u64;
__device__ __align__(1024) __nv_bfloat16 g_xn[SEQ * DM];
__device__ __align__(1024) uint4 g_y[2 * 64 * 2560];
__device__ __align__(1024) __nv_bfloat16 g_abT[DM * 2 * SEQ];
__device__ __align__(1024) __nv_bfloat16 g_z2nT[FH * SEQ];
__device__ __align__(1024) __nv_bfloat16 g_hT[FH * SEQ];
__device__ __align__(128) u64 g_z2stat[4 * SEQ * 2];
enum { FL_AB = 0, FL_Z2N = 128, FL_H = 256, FL_F = 320, FL_XN = 448, FL_COUNT = 576 };
__device__ __align__(128) unsigned g_flags[FL_COUNT * 16];
__device__ unsigned g_ticket;

__device__ __forceinline__ void mbar_init(uint32_t bar, uint32_t cnt) { asm volatile("mbarrier.init.shared::cta.b64 [%0], %1;" :: "r"(bar), "r"(cnt) : "memory"); }
__device__ __forceinline__ void mbar_expect_tx(uint32_t bar, uint32_t bytes) { asm volatile("mbarrier.arrive.expect_tx.shared::cta.b64 _, [%0], %1;" :: "r"(bar), "r"(bytes) : "memory"); }
__device__ __forceinline__ void mbar_arrive(uint32_t bar) { asm volatile("mbarrier.arrive.shared::cta.b64 _, [%0];" :: "r"(bar) : "memory"); }
__device__ __forceinline__ void mbar_arrive_if(uint32_t bar, int live) {
  asm volatile("{\n.reg .pred p;\nsetp.ne.b32 p, %1, 0;\n@p mbarrier.arrive.shared::cta.b64 _, [%0];\n}\n" :: "r"(bar), "r"(live) : "memory");
}
__device__ __forceinline__ void mbar_arrive_cluster(uint32_t bar, uint32_t cta) {
  asm volatile("{\n.reg .b32 ra;\nmapa.shared::cluster.u32 ra, %0, %1;\nmbarrier.arrive.shared::cluster.b64 _, [ra];\n}\n" :: "r"(bar), "r"(cta) : "memory");
}
__device__ __forceinline__ void mbar_wait(uint32_t bar, uint32_t parity) {
  asm volatile("{\n.reg .pred p;\n.reg .u32 c;\nmov.u32 c, 0;\nLAB_WAIT:\n"
               "mbarrier.try_wait.parity.shared::cta.b64 p, [%0], %1;\n@p bra LAB_DONE;\n"
               "add.u32 c, c, 1;\nsetp.lt.u32 p, c, 20000;\n@p bra LAB_WAIT;\nLAB_DONE:\n}\n" :: "r"(bar), "r"(parity) : "memory");
}
__device__ __forceinline__ void tma_load(uint32_t dst, const CUtensorMap* tm, uint32_t bar, int c0, int c1) {
  asm volatile("cp.async.bulk.tensor.2d.shared::cluster.global.mbarrier::complete_tx::bytes [%0], [%1, {%3, %4}], [%2];"
    :: "r"(dst), "l"((uint64_t)tm), "r"(bar), "r"(c0), "r"(c1) : "memory");
}
__device__ __forceinline__ void tma_load_mc(uint32_t dst, const CUtensorMap* tm, uint32_t bar, int c0, int c1, uint64_t policy) {
  asm volatile("cp.async.bulk.tensor.2d.shared::cluster.global.mbarrier::complete_tx::bytes.multicast::cluster.L2::cache_hint [%0], [%1, {%3, %4}], [%2], %5, %6;"
    :: "r"(dst), "l"((uint64_t)tm), "r"(bar), "r"(c0), "r"(c1), "h"((uint16_t)3), "l"(policy) : "memory");
}
__device__ __forceinline__ void bulk_load(uint32_t dst, const void* src, uint32_t bytes, uint32_t bar) {
  asm volatile("cp.async.bulk.shared::cluster.global.mbarrier::complete_tx::bytes [%0], [%1], %2, [%3];"
    :: "r"(dst), "l"((uint64_t)src), "r"(bytes), "r"(bar) : "memory");
}
__device__ __forceinline__ void tma_store(const CUtensorMap* tm, uint32_t src, int c0, int c1, int live) {
  asm volatile("{\n.reg .pred p;\nsetp.ne.b32 p, %4, 0;\n@p cp.async.bulk.tensor.2d.global.shared::cta.bulk_group [%0, {%2, %3}], [%1];\n}\n"
    :: "l"((uint64_t)tm), "r"(src), "r"(c0), "r"(c1), "r"(live) : "memory");
}
__device__ __forceinline__ void bulk_store(void* dst, uint32_t src, uint32_t bytes) {
  asm volatile("cp.async.bulk.global.shared::cta.bulk_group [%0], [%1], %2;" :: "l"(dst), "r"(src), "r"(bytes) : "memory");
}
__device__ __forceinline__ void bulk_commit() { asm volatile("cp.async.bulk.commit_group;" ::: "memory"); }
__device__ __forceinline__ void bulk_wait_read() { asm volatile("cp.async.bulk.wait_group.read 0;" ::: "memory"); }
__device__ __forceinline__ void bulk_wait_all() { asm volatile("cp.async.bulk.wait_group 0;" ::: "memory"); }
__device__ __forceinline__ void cp_async16(uint32_t dst, const void* src) {
  asm volatile("cp.async.cg.shared.global [%0], [%1], 16;" :: "r"(dst), "l"(src) : "memory");
}
__device__ __forceinline__ void cp_async_wait() { asm volatile("cp.async.wait_all;" ::: "memory"); }
__device__ __forceinline__ void prefetch_l2(const void* p) { asm volatile("prefetch.global.L2 [%0];" :: "l"(p)); }
__device__ __forceinline__ void prefetch_tmap(const CUtensorMap* tm) { asm volatile("prefetch.tensormap [%0];" :: "l"((uint64_t)tm) : "memory"); }
__device__ __forceinline__ void fence_async_smem() { asm volatile("fence.proxy.async.shared::cta;" ::: "memory"); }
__device__ __forceinline__ void fence_async_global() { asm volatile("fence.proxy.async.global;" ::: "memory"); }
__device__ __forceinline__ void wgmma_fence() { asm volatile("wgmma.fence.sync.aligned;" ::: "memory"); }
__device__ __forceinline__ void wgmma_commit() { asm volatile("wgmma.commit_group.sync.aligned;" ::: "memory"); }
template<int N> __device__ __forceinline__ void wgmma_wait() { asm volatile("wgmma.wait_group.sync.aligned %0;" :: "n"(N) : "memory"); }
__device__ __forceinline__ void cluster_arrive() { asm volatile("barrier.cluster.arrive.relaxed.aligned;" ::: "memory"); }
__device__ __forceinline__ void cluster_wait() { asm volatile("barrier.cluster.wait.acquire.aligned;" ::: "memory"); }
__device__ __forceinline__ bool elect_one() {
  uint32_t p; asm volatile("{\n.reg .pred p;\nelect.sync _|p, 0xffffffff;\nselp.u32 %0, 1, 0, p;\n}\n" : "=r"(p)); return p;
}
__device__ __forceinline__ void named_sync(int id, int n) { asm volatile("bar.sync %0, %1;" :: "r"(id), "r"(n) : "memory"); }
__device__ __forceinline__ void stmatrix_x4(uint32_t addr, uint32_t r0, uint32_t r1, uint32_t r2, uint32_t r3, int live) {
  asm volatile("{\n.reg .pred p;\nsetp.ne.b32 p, %5, 0;\n@p stmatrix.sync.aligned.m8n8.x4.shared.b16 [%0], {%1, %2, %3, %4};\n}\n"
    :: "r"(addr), "r"(r0), "r"(r1), "r"(r2), "r"(r3), "r"(live) : "memory");
}
__device__ __forceinline__ void stmatrix_x4_t(uint32_t addr, uint32_t r0, uint32_t r1, uint32_t r2, uint32_t r3, int live) {
  asm volatile("{\n.reg .pred p;\nsetp.ne.b32 p, %5, 0;\n@p stmatrix.sync.aligned.m8n8.x4.trans.shared.b16 [%0], {%1, %2, %3, %4};\n}\n"
    :: "r"(addr), "r"(r0), "r"(r1), "r"(r2), "r"(r3), "r"(live) : "memory");
}
__device__ __forceinline__ void ldmatrix_x4_t(uint32_t addr, uint32_t (&r)[4], int live) {
  asm volatile("{\n.reg .pred p;\nsetp.ne.b32 p, %5, 0;\n@p ldmatrix.sync.aligned.m8n8.x4.trans.shared.b16 {%0, %1, %2, %3}, [%4];\n}\n"
    : "=r"(r[0]), "=r"(r[1]), "=r"(r[2]), "=r"(r[3]) : "r"(addr), "r"(live) : "memory");
}
__device__ __forceinline__ void sts128u(uint32_t addr, uint32_t a, uint32_t b, uint32_t c, uint32_t d, int live) {
  asm volatile("{\n.reg .pred p;\nsetp.ne.b32 p, %5, 0;\n@p st.shared.v4.b32 [%0], {%1, %2, %3, %4};\n}\n" :: "r"(addr), "r"(a), "r"(b), "r"(c), "r"(d), "r"(live) : "memory");
}
__device__ __forceinline__ void stg128(void* p, uint4 v, int live) {
  asm volatile("{\n.reg .pred p;\nsetp.ne.b32 p, %5, 0;\n@p st.global.v4.b32 [%0], {%1, %2, %3, %4};\n}\n" :: "l"(p), "r"(v.x), "r"(v.y), "r"(v.z), "r"(v.w), "r"(live) : "memory");
}
__device__ __forceinline__ uint4 lds128u(uint32_t addr) {
  uint4 v; asm volatile("ld.shared.v4.u32 {%0, %1, %2, %3}, [%4];" : "=r"(v.x), "=r"(v.y), "=r"(v.z), "=r"(v.w) : "r"(addr) : "memory"); return v;
}
__device__ __forceinline__ void sts32(uint32_t addr, float a) { asm volatile("st.shared.f32 [%0], %1;" :: "r"(addr), "f"(a) : "memory"); }
__device__ __forceinline__ float lds32(uint32_t addr) { float v; asm volatile("ld.shared.f32 %0, [%1];" : "=f"(v) : "r"(addr) : "memory"); return v; }
__device__ __forceinline__ uint32_t pack_bf16(float lo, float hi) {
  uint32_t r; asm("cvt.rn.bf16x2.f32 %0, %1, %2;" : "=r"(r) : "f"(hi), "f"(lo)); return r;
}
__device__ __forceinline__ uint32_t mul_bf16x2(uint32_t a, uint32_t b) {
  uint32_t r; asm("mul.rn.bf16x2 %0, %1, %2;" : "=r"(r) : "r"(a), "r"(b)); return r;
}
__device__ __forceinline__ uint32_t add_bf16x2(uint32_t a, uint32_t b) {
  uint32_t r; asm("add.rn.bf16x2 %0, %1, %2;" : "=r"(r) : "r"(a), "r"(b)); return r;
}
__device__ __forceinline__ float bf_lo(uint32_t v) { return __uint_as_float(v << 16); }
__device__ __forceinline__ float bf_hi(uint32_t v) { return __uint_as_float(v & 0xffff0000u); }

__device__ __forceinline__ u64 tagged(float v, unsigned tag) { return ((u64)tag << 32) | __float_as_uint(v); }
__device__ __forceinline__ void st_tag2(u64* p, u64 a, u64 b, int live) {
  asm volatile("{\n.reg .pred p;\nsetp.ne.b32 p, %3, 0;\n@p st.relaxed.gpu.global.v2.b64 [%0], {%1, %2};\n}\n" :: "l"(p), "l"(a), "l"(b), "r"(live) : "memory");
}
__device__ __forceinline__ uint4 ld_tag2(const u64* p, int live) {
  u64 a = 0, b = 0;
  asm volatile("{\n.reg .pred p;\nsetp.ne.b32 p, %3, 0;\n@p ld.relaxed.gpu.global.v2.b64 {%0, %1}, [%2];\n}\n" : "+l"(a), "+l"(b) : "l"(p), "r"(live) : "memory");
  return make_uint4((uint32_t)a, (uint32_t)(a >> 32), (uint32_t)b, (uint32_t)(b >> 32));
}
__device__ __forceinline__ void flag_set(int id, unsigned tag) {
  asm volatile("fence.proxy.async.global;\nfence.acq_rel.gpu;\nst.relaxed.gpu.global.u32 [%0], %1;" :: "l"(g_flags + id * 16), "r"(tag) : "memory");
}
__device__ __forceinline__ unsigned flag_get(int id) {
  unsigned v;
  asm volatile("ld.acquire.gpu.global.u32 %0, [%1];" : "=r"(v) : "l"(g_flags + id * 16) : "memory"); return v;
}
constexpr int SPIN_MAX = 2000000;
constexpr int PF_W = 2500, PF_X = 34000;

__device__ __forceinline__ float gelu2(float v) {
  const float K1 = 0.7978845608f, K2 = 0.7978845608f * 0.044715f;
  float a = v * fmaf(v * v, K2, K1);
  float t; asm("tanh.approx.f32 %0, %1;" : "=f"(t) : "f"(a));
  return fmaf(v, t, v);
}

template<int N, int TA, int TB> struct Wgmma;
template<int TA, int TB> struct Wgmma<160, TA, TB> {
  static __device__ __forceinline__ void mma(float (&d)[80], uint64_t da, uint64_t db, int scale_d) {
    asm volatile("{\n.reg .pred p;\nsetp.ne.b32 p, %82, 0;\n"
      "wgmma.mma_async.sync.aligned.m64n160k16.f32.bf16.bf16 {%0, %1, %2, %3, %4, %5, %6, %7, %8, %9, %10, %11, %12, %13, %14, %15, %16, %17, %18, %19, %20, %21, %22, %23, %24, %25, %26, %27, %28, %29, %30, %31, %32, %33, %34, %35, %36, %37, %38, %39, %40, %41, %42, %43, %44, %45, %46, %47, %48, %49, %50, %51, %52, %53, %54, %55, %56, %57, %58, %59, %60, %61, %62, %63, %64, %65, %66, %67, %68, %69, %70, %71, %72, %73, %74, %75, %76, %77, %78, %79}, %80, %81, p, 1, 1, %83, %84;\n}\n"
      : "+f"(d[0]), "+f"(d[1]), "+f"(d[2]), "+f"(d[3]), "+f"(d[4]), "+f"(d[5]), "+f"(d[6]), "+f"(d[7]), "+f"(d[8]), "+f"(d[9]), "+f"(d[10]), "+f"(d[11]), "+f"(d[12]), "+f"(d[13]), "+f"(d[14]), "+f"(d[15]), "+f"(d[16]), "+f"(d[17]), "+f"(d[18]), "+f"(d[19]), "+f"(d[20]), "+f"(d[21]), "+f"(d[22]), "+f"(d[23]), "+f"(d[24]), "+f"(d[25]), "+f"(d[26]), "+f"(d[27]), "+f"(d[28]), "+f"(d[29]), "+f"(d[30]), "+f"(d[31]), "+f"(d[32]), "+f"(d[33]), "+f"(d[34]), "+f"(d[35]), "+f"(d[36]), "+f"(d[37]), "+f"(d[38]), "+f"(d[39]), "+f"(d[40]), "+f"(d[41]), "+f"(d[42]), "+f"(d[43]), "+f"(d[44]), "+f"(d[45]), "+f"(d[46]), "+f"(d[47]), "+f"(d[48]), "+f"(d[49]), "+f"(d[50]), "+f"(d[51]), "+f"(d[52]), "+f"(d[53]), "+f"(d[54]), "+f"(d[55]), "+f"(d[56]), "+f"(d[57]), "+f"(d[58]), "+f"(d[59]), "+f"(d[60]), "+f"(d[61]), "+f"(d[62]), "+f"(d[63]), "+f"(d[64]), "+f"(d[65]), "+f"(d[66]), "+f"(d[67]), "+f"(d[68]), "+f"(d[69]), "+f"(d[70]), "+f"(d[71]), "+f"(d[72]), "+f"(d[73]), "+f"(d[74]), "+f"(d[75]), "+f"(d[76]), "+f"(d[77]), "+f"(d[78]), "+f"(d[79])
      : "l"(da), "l"(db), "r"(scale_d), "n"(TA), "n"(TB));
  }
  static __device__ __forceinline__ void mma_first(float (&d)[80], uint64_t da, uint64_t db) {
    asm volatile("{\n.reg .pred p;\nsetp.ne.b32 p, 0, 0;\n"
      "wgmma.mma_async.sync.aligned.m64n160k16.f32.bf16.bf16 {%0, %1, %2, %3, %4, %5, %6, %7, %8, %9, %10, %11, %12, %13, %14, %15, %16, %17, %18, %19, %20, %21, %22, %23, %24, %25, %26, %27, %28, %29, %30, %31, %32, %33, %34, %35, %36, %37, %38, %39, %40, %41, %42, %43, %44, %45, %46, %47, %48, %49, %50, %51, %52, %53, %54, %55, %56, %57, %58, %59, %60, %61, %62, %63, %64, %65, %66, %67, %68, %69, %70, %71, %72, %73, %74, %75, %76, %77, %78, %79}, %80, %81, p, 1, 1, %82, %83;\n}\n"
      : "=f"(d[0]), "=f"(d[1]), "=f"(d[2]), "=f"(d[3]), "=f"(d[4]), "=f"(d[5]), "=f"(d[6]), "=f"(d[7]), "=f"(d[8]), "=f"(d[9]), "=f"(d[10]), "=f"(d[11]), "=f"(d[12]), "=f"(d[13]), "=f"(d[14]), "=f"(d[15]), "=f"(d[16]), "=f"(d[17]), "=f"(d[18]), "=f"(d[19]), "=f"(d[20]), "=f"(d[21]), "=f"(d[22]), "=f"(d[23]), "=f"(d[24]), "=f"(d[25]), "=f"(d[26]), "=f"(d[27]), "=f"(d[28]), "=f"(d[29]), "=f"(d[30]), "=f"(d[31]), "=f"(d[32]), "=f"(d[33]), "=f"(d[34]), "=f"(d[35]), "=f"(d[36]), "=f"(d[37]), "=f"(d[38]), "=f"(d[39]), "=f"(d[40]), "=f"(d[41]), "=f"(d[42]), "=f"(d[43]), "=f"(d[44]), "=f"(d[45]), "=f"(d[46]), "=f"(d[47]), "=f"(d[48]), "=f"(d[49]), "=f"(d[50]), "=f"(d[51]), "=f"(d[52]), "=f"(d[53]), "=f"(d[54]), "=f"(d[55]), "=f"(d[56]), "=f"(d[57]), "=f"(d[58]), "=f"(d[59]), "=f"(d[60]), "=f"(d[61]), "=f"(d[62]), "=f"(d[63]), "=f"(d[64]), "=f"(d[65]), "=f"(d[66]), "=f"(d[67]), "=f"(d[68]), "=f"(d[69]), "=f"(d[70]), "=f"(d[71]), "=f"(d[72]), "=f"(d[73]), "=f"(d[74]), "=f"(d[75]), "=f"(d[76]), "=f"(d[77]), "=f"(d[78]), "=f"(d[79])
      : "l"(da), "l"(db), "n"(TA), "n"(TB));
  }
};
template<int TA, int TB> struct Wgmma<192, TA, TB> {
  static __device__ __forceinline__ void mma(float (&d)[96], uint64_t da, uint64_t db, int scale_d) {
    asm volatile("{\n.reg .pred p;\nsetp.ne.b32 p, %98, 0;\n"
      "wgmma.mma_async.sync.aligned.m64n192k16.f32.bf16.bf16 {%0, %1, %2, %3, %4, %5, %6, %7, %8, %9, %10, %11, %12, %13, %14, %15, %16, %17, %18, %19, %20, %21, %22, %23, %24, %25, %26, %27, %28, %29, %30, %31, %32, %33, %34, %35, %36, %37, %38, %39, %40, %41, %42, %43, %44, %45, %46, %47, %48, %49, %50, %51, %52, %53, %54, %55, %56, %57, %58, %59, %60, %61, %62, %63, %64, %65, %66, %67, %68, %69, %70, %71, %72, %73, %74, %75, %76, %77, %78, %79, %80, %81, %82, %83, %84, %85, %86, %87, %88, %89, %90, %91, %92, %93, %94, %95}, %96, %97, p, 1, 1, %99, %100;\n}\n"
      : "+f"(d[0]), "+f"(d[1]), "+f"(d[2]), "+f"(d[3]), "+f"(d[4]), "+f"(d[5]), "+f"(d[6]), "+f"(d[7]), "+f"(d[8]), "+f"(d[9]), "+f"(d[10]), "+f"(d[11]), "+f"(d[12]), "+f"(d[13]), "+f"(d[14]), "+f"(d[15]), "+f"(d[16]), "+f"(d[17]), "+f"(d[18]), "+f"(d[19]), "+f"(d[20]), "+f"(d[21]), "+f"(d[22]), "+f"(d[23]), "+f"(d[24]), "+f"(d[25]), "+f"(d[26]), "+f"(d[27]), "+f"(d[28]), "+f"(d[29]), "+f"(d[30]), "+f"(d[31]), "+f"(d[32]), "+f"(d[33]), "+f"(d[34]), "+f"(d[35]), "+f"(d[36]), "+f"(d[37]), "+f"(d[38]), "+f"(d[39]), "+f"(d[40]), "+f"(d[41]), "+f"(d[42]), "+f"(d[43]), "+f"(d[44]), "+f"(d[45]), "+f"(d[46]), "+f"(d[47]), "+f"(d[48]), "+f"(d[49]), "+f"(d[50]), "+f"(d[51]), "+f"(d[52]), "+f"(d[53]), "+f"(d[54]), "+f"(d[55]), "+f"(d[56]), "+f"(d[57]), "+f"(d[58]), "+f"(d[59]), "+f"(d[60]), "+f"(d[61]), "+f"(d[62]), "+f"(d[63]), "+f"(d[64]), "+f"(d[65]), "+f"(d[66]), "+f"(d[67]), "+f"(d[68]), "+f"(d[69]), "+f"(d[70]), "+f"(d[71]), "+f"(d[72]), "+f"(d[73]), "+f"(d[74]), "+f"(d[75]), "+f"(d[76]), "+f"(d[77]), "+f"(d[78]), "+f"(d[79]), "+f"(d[80]), "+f"(d[81]), "+f"(d[82]), "+f"(d[83]), "+f"(d[84]), "+f"(d[85]), "+f"(d[86]), "+f"(d[87]), "+f"(d[88]), "+f"(d[89]), "+f"(d[90]), "+f"(d[91]), "+f"(d[92]), "+f"(d[93]), "+f"(d[94]), "+f"(d[95])
      : "l"(da), "l"(db), "r"(scale_d), "n"(TA), "n"(TB));
  }
  static __device__ __forceinline__ void mma_first(float (&d)[96], uint64_t da, uint64_t db) {
    asm volatile("{\n.reg .pred p;\nsetp.ne.b32 p, 0, 0;\n"
      "wgmma.mma_async.sync.aligned.m64n192k16.f32.bf16.bf16 {%0, %1, %2, %3, %4, %5, %6, %7, %8, %9, %10, %11, %12, %13, %14, %15, %16, %17, %18, %19, %20, %21, %22, %23, %24, %25, %26, %27, %28, %29, %30, %31, %32, %33, %34, %35, %36, %37, %38, %39, %40, %41, %42, %43, %44, %45, %46, %47, %48, %49, %50, %51, %52, %53, %54, %55, %56, %57, %58, %59, %60, %61, %62, %63, %64, %65, %66, %67, %68, %69, %70, %71, %72, %73, %74, %75, %76, %77, %78, %79, %80, %81, %82, %83, %84, %85, %86, %87, %88, %89, %90, %91, %92, %93, %94, %95}, %96, %97, p, 1, 1, %98, %99;\n}\n"
      : "=f"(d[0]), "=f"(d[1]), "=f"(d[2]), "=f"(d[3]), "=f"(d[4]), "=f"(d[5]), "=f"(d[6]), "=f"(d[7]), "=f"(d[8]), "=f"(d[9]), "=f"(d[10]), "=f"(d[11]), "=f"(d[12]), "=f"(d[13]), "=f"(d[14]), "=f"(d[15]), "=f"(d[16]), "=f"(d[17]), "=f"(d[18]), "=f"(d[19]), "=f"(d[20]), "=f"(d[21]), "=f"(d[22]), "=f"(d[23]), "=f"(d[24]), "=f"(d[25]), "=f"(d[26]), "=f"(d[27]), "=f"(d[28]), "=f"(d[29]), "=f"(d[30]), "=f"(d[31]), "=f"(d[32]), "=f"(d[33]), "=f"(d[34]), "=f"(d[35]), "=f"(d[36]), "=f"(d[37]), "=f"(d[38]), "=f"(d[39]), "=f"(d[40]), "=f"(d[41]), "=f"(d[42]), "=f"(d[43]), "=f"(d[44]), "=f"(d[45]), "=f"(d[46]), "=f"(d[47]), "=f"(d[48]), "=f"(d[49]), "=f"(d[50]), "=f"(d[51]), "=f"(d[52]), "=f"(d[53]), "=f"(d[54]), "=f"(d[55]), "=f"(d[56]), "=f"(d[57]), "=f"(d[58]), "=f"(d[59]), "=f"(d[60]), "=f"(d[61]), "=f"(d[62]), "=f"(d[63]), "=f"(d[64]), "=f"(d[65]), "=f"(d[66]), "=f"(d[67]), "=f"(d[68]), "=f"(d[69]), "=f"(d[70]), "=f"(d[71]), "=f"(d[72]), "=f"(d[73]), "=f"(d[74]), "=f"(d[75]), "=f"(d[76]), "=f"(d[77]), "=f"(d[78]), "=f"(d[79]), "=f"(d[80]), "=f"(d[81]), "=f"(d[82]), "=f"(d[83]), "=f"(d[84]), "=f"(d[85]), "=f"(d[86]), "=f"(d[87]), "=f"(d[88]), "=f"(d[89]), "=f"(d[90]), "=f"(d[91]), "=f"(d[92]), "=f"(d[93]), "=f"(d[94]), "=f"(d[95])
      : "l"(da), "l"(db), "n"(TA), "n"(TB));
  }
};


__device__ __forceinline__ uint64_t make_desc(uint32_t addr, uint32_t lbo, uint32_t sbo, uint32_t swz) {
  return (uint64_t)((addr & 0x3FFFF) >> 4) | ((uint64_t)(lbo >> 4) << 16) | ((uint64_t)(sbo >> 4) << 32) | ((uint64_t)swz << 62);
}

enum { B_FULL = 0, B_EMPTY = STAGES, B_SFREE = 2 * STAGES, B_SFREE1, B_Z1RDY, B_TURN0, B_TURN1, B_TAB, B_OWN, B_OWN1, B_PREV, B_TAG, B_STORE, B_STORE1, B_XN, B_SFREE2, B_FULL2, B_EMPTY2 = B_FULL2 + 4, B_DEP = B_EMPTY2 + 4, B_COUNT = B_DEP + 8 };

template<int V> struct IC { static constexpr int value = V; };
struct Ctx {
  uint32_t base;
  int warp, lane;
  __device__ __forceinline__ uint32_t bar(int i) const { return base + BAR_OFF + 8 * i; }
  __device__ __forceinline__ uint32_t ext(int off) const { return base + EXT_OFF + off; }
  __device__ __forceinline__ unsigned tag() const { mbar_wait(bar(B_TAG), 0); return __float_as_uint(lds32(ext(X_TAG))); }
};

__device__ __forceinline__ void release_stage(const Ctx& c, int it) {
  if (c.lane < 2) mbar_arrive_cluster(c.bar(B_EMPTY + (it & (STAGES - 1))), c.lane);
}

template<int N, int TA, int TB, bool ZI, int OWN = 0, int NOWN = 0>
__device__ __forceinline__ void mainloop(const Ctx& c, float (&acc)[2][N / 2], int it0, int n, bool pend, uint32_t pass_bar) {
  wgmma_fence();
  #pragma unroll 1
  for (int k = 0; k < n; k++) {
    int it = it0 + k, s = it & (STAGES - 1);
    mbar_wait(c.bar(B_FULL + s), (it / STAGES) & 1);
    if (pass_bar && k == n - 1 && c.lane == 0 && c.warp == 0) mbar_arrive(pass_bar);
    uint32_t sa = c.base + s * STAGE_BYTES, sb = sa + A_BYTES, mstep = 512;
    if (OWN == 1 && k < NOWN) sb = c.base + SBUF_OFF + k * (192 * 128);
    if (OWN == 2 && k < NOWN) { sa = c.base + SBUF_OFF + k * 8192; mstep = 192 * 128 / 16; }
    uint64_t da = make_desc(sa, TA == 0 ? 16 : 8192, 1024, 1);
    uint64_t db = make_desc(sb, TB == 0 ? 16 : 8192, 1024, 1);
    wgmma_fence();
    #pragma unroll
    for (int kk = 0; kk < 4; kk++) {
      int sd = (ZI && k == 0 && kk == 0) ? 0 : 1;
      #pragma unroll
      for (int mb = 0; mb < 2; mb++)
        Wgmma<N, TA, TB>::mma(acc[mb], da + (uint64_t)(mb * mstep + (TA == 0 ? kk * 2 : kk * 128)), db + (uint64_t)(TB == 0 ? kk * 2 : kk * 128), sd);
    }
    wgmma_commit();
    wgmma_wait<1>();
    if (k > 0 || pend) release_stage(c, it - 1);
    if (OWN && k == NOWN && c.lane == 0) mbar_arrive(c.bar(B_OWN + OWN - 1));
  }
}
template<int N>
__device__ __forceinline__ void fence_acc(float (&acc)[2][N / 2]) {
  #pragma unroll
  for (int mb = 0; mb < 2; mb++)
    #pragma unroll
    for (int e = 0; e < N / 2; e++) asm volatile("" : "+f"(acc[mb][e]) :: "memory");
}
template<int N>
__device__ __forceinline__ void drain(const Ctx& c, float (&acc)[2][N / 2], int it_last) {
  wgmma_wait<0>();
  fence_acc<N>(acc);
  release_stage(c, it_last);
}
template<int N>
__device__ __forceinline__ void first_bias(const Ctx& c, float (&acc)[2][N / 2]) {
  mbar_wait(c.bar(B_TAB), 0);
  uint64_t da = make_desc(c.ext(X_A), 2048, 128, 0), db = make_desc(c.ext(X_ONES), 0, 0, 0);
  wgmma_fence();
  Wgmma<N, 0, 0>::mma_first(acc[0], da, db);
  Wgmma<N, 0, 0>::mma_first(acc[1], da + 64, db);
  wgmma_commit();
}

__device__ __forceinline__ uint32_t stage_t_addr(const Ctx& c) {
  int mi = c.lane >> 3, r = c.lane & 7;
  return c.base + SBUF_OFF + ((mi >> 1) * 8 + r) * 128 + (((2 * c.warp + (mi & 1)) ^ r) << 4);
}

__global__ void __cluster_dims__(2, 1, 1) __launch_bounds__(384, 1)
fused_kernel(const __grid_constant__ Maps maps, const __nv_bfloat16* __restrict__ x, const __nv_bfloat16* __restrict__ hre,
             const __nv_bfloat16* __restrict__ him, const __nv_bfloat16* __restrict__ win, const __nv_bfloat16* __restrict__ wout,
             const __nv_bfloat16* __restrict__ bsp) {
  Ctx c;
  asm("mov.u32 %0, smem_raw;" : "=r"(c.base));
  if (threadIdx.x == 1023) smem_raw[0] = 0;
  const int wg = __shfl_sync(0xffffffffu, threadIdx.x >> 7, 0), tid = threadIdx.x & 127;
  c.warp = __shfl_sync(0xffffffffu, tid >> 5, 0); c.lane = tid & 31;
  const int cta = blockIdx.x, rank = cta & 1, pair = cta >> 1;
  const bool isG = (pair >> 3) & 1;
  const int q = (pair >> 4) * 8 + (pair & 7), rb = q >> 1, ct = (q & 1) * 2 + rank;
  const int row0 = rb * 128;
  const uint32_t sbuf = c.base + SBUF_OFF;

  const int xrow = row0 + ((isG ? 4 : 0) + ct) * 16;
  const uint32_t xa = sbuf + (threadIdx.x >> 4) * 1280 + (threadIdx.x & 15) * 16;
  if (wg < 2) {
    #pragma unroll
    for (int i = 0; i < 5; i++) cp_async16(xa + i * 256, x + (size_t)(xrow + (threadIdx.x >> 4)) * DM + (threadIdx.x & 15) * 8 + i * 128);
  }
  if (threadIdx.x == 256) {
    #pragma unroll
    for (int s = 0; s < B_COUNT; s++)
      mbar_init(c.bar(s), (s >= B_EMPTY && s < B_EMPTY + STAGES) ? 8 : (s == B_Z1RDY || s == B_STORE || s == B_STORE1) ? 128 : s == B_TAB ? 32 : (s == B_OWN || s == B_OWN1) ? 4 : s == B_XN ? 256 : (s >= B_EMPTY2 && s < B_EMPTY2 + 4) ? 16 : s == B_SFREE2 ? 2 : 1);
    asm volatile("fence.mbarrier_init.release.cluster;" ::: "memory");
  } else if (threadIdx.x >= 288 && threadIdx.x < 288 + M_COUNT) {
    prefetch_tmap(&maps.m[threadIdx.x - 288]);
  }
  __syncwarp();
  cluster_arrive();

  if (wg == 2) {
    asm volatile("setmaxnreg.dec.sync.aligned.u32 40;");
    if (c.warp == 0) {
      int it = 0;
      uint64_t pol_stream, pol_normal;
      asm("createpolicy.fractional.L2::evict_normal.b64 %0, 1.0;" : "=l"(pol_normal));
      asm("createpolicy.fractional.L2::evict_first.b64 %0, 1.0;" : "=l"(pol_stream));
      auto wait_dep = [&](int d) {
        mbar_wait(c.bar(B_DEP + d), 0);
        fence_async_global();
      };
      auto wait_box = [&](int r) {
        #pragma unroll 1
        for (int sp = 0; sp < SPIN_MAX; sp++) {
          unsigned m; asm volatile("ld.acquire.cta.shared.u32 %0, [%1];" : "=r"(m) : "r"(c.ext(X_MASK)) : "memory");
          if ((m >> r) & 1) break;
        }
        fence_async_global();
      };
      auto run = [&](auto mode_c, const CUtensorMap* ma, const CUtensorMap* mb, int ka, int kb, int ks, int skip, int k0, int n, int nb0, uint32_t bytes, int fl) {
        constexpr int MODE = decltype(mode_c)::value;
        #pragma unroll 1
        for (int k = k0; k < n; k++, it++) {
          const int s = it & (STAGES - 1), ko = (k + (k >= skip ? 1 : 0)) * ks;
          const uint32_t sa = c.base + s * STAGE_BYTES, fb = c.bar(B_FULL + s);
          mbar_wait(c.bar(B_EMPTY + s), ((it / STAGES) & 1) ^ 1);
          if (elect_one()) {
            mbar_expect_tx(fb, bytes);
            tma_load_mc(sa + rank * 8192, ma, fb, ka + ko, row0 + rank * 64, (it < 20 || fl == 1) ? pol_normal : pol_stream);
            if (MODE == 1) {
              #pragma unroll
              for (int b = 0; b < 3; b++) tma_load(sa + A_BYTES + b * 8192, mb, fb, nb0 + b * 64, ko);
            }
          }
          if (MODE == 0) {
            if (fl == 1) wait_box(k + (k >= skip ? 1 : 0));
            else if (k == 0 && fl >= 0) wait_dep(fl);
            if (elect_one()) tma_load(sa + A_BYTES, mb, fb, kb + ko, nb0);
          }
        }
      };
      constexpr uint32_t B160 = A_BYTES + 160 * 128, B192 = A_BYTES + 192 * 128;
      if (elect_one()) {
        #pragma unroll
        for (int s = 0; s < STAGES; s++) {
          const uint32_t sb = c.base + s * STAGE_BYTES + A_BYTES, fb = c.bar(B_FULL + s);
          mbar_expect_tx(fb, isG ? B192 : B160);
          if (isG) {
            #pragma unroll
            for (int b = 0; b < 3; b++) tma_load(sb + b * 8192, &maps.m[M_WIN], fb, FH + ct * 192 + b * 64, s * 64);
          } else tma_load(sb, &maps.m[M_HRE], fb, s * 64, ct * 160);
        }
      }
      cluster_wait();
      wait_dep(0);
      if (elect_one()) {
        #pragma unroll
        for (int s = 0; s < STAGES; s++) tma_load_mc(c.base + s * STAGE_BYTES + rank * 8192, &maps.m[M_X], c.bar(B_FULL + s), s * 64, row0 + rank * 64, pol_normal);
      }
      it = STAGES;
      if (isG) {
        #pragma unroll 1
        for (int t = 0; t < 2; t++) run(IC<1>(), &maps.m[M_X], &maps.m[M_WIN], 0, 0, 64, 99, t ? 0 : STAGES, 10, (t ? 0 : FH) + ct * 192, B192, -1);
        run(IC<2>(), &maps.m[M_WSP], &maps.m[M_WSP], row0, 0, 64, 99, 0, 2, 0, A_BYTES, -1);
      }
      #pragma unroll 1
      for (int sg = 0; sg < (isG ? 3 : 2); sg++) {
        const CUtensorMap *ma, *mb; int ka = 0, kb = 0, ks = 64, skip = 99, n, nb0 = ct * 160, fl = -1; uint32_t bytes = B160;
        if (!isG) {
          ma = &maps.m[M_X]; mb = &maps.m[M_HRE + sg]; n = 10;
        } else if (sg < 2) {
          ma = &maps.m[M_WSP]; mb = &maps.m[M_Z2NT]; n = 15; ka = kb = sg * 64; ks = 128; skip = rb; nb0 = ct * 192; fl = 1 + sg; bytes = B192;
        } else {
          #pragma unroll 1
          for (int k = 0; k < 2; k++, it++) {
            const int s = it & (STAGES - 1);
            mbar_wait(c.bar(B_EMPTY + s), ((it / STAGES) & 1) ^ 1);
            if (elect_one()) {
              mbar_expect_tx(c.bar(B_FULL + s), 192 * 128);
              #pragma unroll
              for (int b = 0; b < 3; b++) tma_load(c.base + s * STAGE_BYTES + A_BYTES + b * 8192, &maps.m[M_XB], c.bar(B_FULL + s), ct * 160 + b * 64, row0 + k * 64);
            }
          }
          ma = &maps.m[M_SIM]; mb = &maps.m[M_ABT]; n = JSPLIT; ka = (32 - JSPLIT) * 64; kb = SEQ + ka; fl = 3;
        }
        run(IC<0>(), ma, mb, ka, kb, ks, skip, (!isG && sg == 0) ? STAGES : 0, n, nb0, bytes, fl);
      }
      if (!isG) {
        const int half = rb & 1;
        #pragma unroll 1
        for (int k = 0; k < NY + YSOLO; k++) {
          const int s = k & 3, im = k >= 16;
          const int kc = (k >= NY ? k - 16 : im ? half * (NY - 16 + YSOLO) + k - 16 : half * 16 + k) * 64;
          const uint32_t sa = c.base + s * STAGE2_BYTES, fb = c.bar(B_FULL2 + s);
          if (k < 3) { if (k == 0) mbar_wait(c.bar(B_EMPTY), 0); mbar_wait(c.bar(B_EMPTY + k + 1), 0); }
          else if (k == 3) mbar_wait(c.bar(B_SFREE2), 0);
          else mbar_wait(c.bar(B_EMPTY2 + s), ((k >> 2) & 1) ^ 1);
          if (elect_one()) {
            mbar_expect_tx(fb, k < NY ? STAGE2_BYTES : B160);
            if (k < NY) tma_load_mc(sa + rank * 16384, &maps.m[M_SRE2 + im], fb, kc, (rb >> 1) * 256 + rank * 128, pol_stream);
            else tma_load_mc(sa + half * 16384 + rank * 8192, &maps.m[M_SIM], fb, kc, row0 + rank * 64, pol_stream);
          }
          if (k < 16) { if (!(k & 1)) wait_box(half * 8 + (k >> 1)); }
          else if (k == 16) wait_dep(2);
          if (elect_one()) tma_load(sa + 32768, &maps.m[M_ABT], fb, im * SEQ + kc, ct * 160);
        }
      }
      if (isG) {
        #pragma unroll 1
        for (int k = 0; k < 12; k++, it++) {
          const int s = it & (STAGES - 1);
          const int f0 = k < 6 ? (ct ^ (k >= 3 ? 1 : 0)) * 192 + (k % 3) * 64 : ((ct >> 1) ^ 1) * 384 + (k - 6) * 64;
          const uint32_t sa = c.base + s * STAGE_BYTES, fb = c.bar(B_FULL + s);
          mbar_wait(c.bar(B_EMPTY + s), ((it / STAGES) & 1) ^ 1);
          if (elect_one()) {
            mbar_expect_tx(fb, k < 3 ? 192 * 128 : B192);
            #pragma unroll
            for (int b = 0; b < 3; b++) tma_load(sa + A_BYTES + b * 8192, &maps.m[M_WOUT], fb, ct * 160 + b * 64, f0);
          }
          if (k == 3) wait_dep(4);
          if (k == 6) wait_dep(5);
          if (k >= 3 && elect_one()) {
            if (k < 6) { tma_load(sa, &maps.m[M_HTLD], fb, row0, f0); tma_load(sa + 8192, &maps.m[M_HTLD], fb, row0 + 64, f0); }
            else tma_load_mc(sa + rank * 8192, &maps.m[M_HTLD], fb, row0 + rank * 64, f0, pol_normal);
          }
        }
        mbar_wait(c.bar(B_EMPTY + (IT_Y & 3)), ((IT_Y / STAGES) & 1) ^ 1);
        wait_dep(7);
        if (elect_one()) {
          mbar_expect_tx(c.bar(B_FULL + (IT_Y & 3)), STAGE_BYTES);
          bulk_load(c.base + (IT_Y & 3) * STAGE_BYTES, g_y + (size_t)(64 + rb * 4 + ct) * 2560, STAGE_BYTES, c.bar(B_FULL + (IT_Y & 3)));
        }
      }
    } else {
      const int ht = tid - 32;
      unsigned tk = 0;
      if (ht == 0) tk = atomicAdd(&g_ticket, 1u);
      if (c.warp == 2) {
        #pragma unroll
        for (int j = 0; j < 4; j++) {
          const int i = c.lane + j * 32;
          sts128u(c.ext(X_A) + i * 16, pack_bf16(0.5f * __bfloat162float(bsp[row0 + i]), 0.f), 0, 0, 0, 1);
          sts128u(c.ext(X_Z) + i * 16, 0, 0, 0, 0, 1);
        }
        sts128u(c.ext(X_ONES) + (ht & 7) * 16, 0x00003F80u, 0, 0, 0, ht < 40);
        #pragma unroll 1
        for (int i = c.lane; i < 512; i += 32) {
          const int r = i >> 3, ch = (i & 7) ^ (r & 7), e = ch == (r >> 3) ? (r & 7) : 8;
          const uint32_t one = (e & 1) ? 0x3F800000u : 0x00003F80u;
          sts128u(c.ext(X_ID) + i * 16, (e >> 1) == 0 ? one : 0, (e >> 1) == 1 ? one : 0, (e >> 1) == 2 ? one : 0, (e >> 1) == 3 ? one : 0, 1);
        }
        fence_async_smem();
      }
      cluster_wait();
      if (ht == 0) { sts32(c.ext(X_MASK), 0.f); sts32(c.ext(X_TAG), __uint_as_float((tk >> 7) + 1u)); mbar_arrive(c.bar(B_TAG)); }
      if (c.warp == 2) mbar_arrive(c.bar(B_TAB));
      __syncwarp();
      const unsigned tag = c.tag();
      if (c.warp == 1) {
        mbar_wait(c.bar(B_XN), 0);
        if (c.lane == 0) { flag_set(FL_XN + rb * 8 + (isG ? 4 : 0) + ct, tag); }
      }
      __syncwarp();
      if (c.warp == 3) {
        #pragma unroll 1
        for (int d = 0; d < (isG ? 8 : 3); d++) {
          const int fl = d == 0 ? FL_XN + rb * 8 + rank * 4 : !isG ? FL_AB + ((d - 1) * 4 + ct) * 16 : d < 3 ? FL_Z2N + (ct * 2 + d - 1) * 16
                         : d == 3 ? FL_AB + (4 + ct) * 16 : d == 4 ? FL_H + rb * 4 + (ct ^ 1) : d == 5 ? FL_H + rb * 4 + ((ct >> 1) ^ 1) * 2 : FL_F + (rb * 4 + ct) * 2 + d - 6;
          const int nfl = d == 0 ? 4 : d < 4 ? 16 : d == 5 ? 2 : 1;
          #pragma unroll 1
          for (int sp = 0; sp < SPIN_MAX; sp++) {
            const unsigned rdy = __ballot_sync(0xffffffffu, flag_get(fl + (c.lane & (nfl - 1))) == tag);
            if (d == 1 && c.lane == 0) asm volatile("st.release.cta.shared.u32 [%0], %1;" :: "r"(c.ext(X_MASK)), "r"(rdy) : "memory");
            if (rdy == 0xffffffffu) break;
          }
          if (c.lane == 0) mbar_arrive(c.bar(B_DEP + d));
          if (d == 6) {
            mbar_wait(c.bar(B_SFREE1), 0); mbar_wait(c.bar(B_OWN1), 0);
            fence_async_global();
            if (elect_one()) {
              mbar_expect_tx(c.bar(B_PREV), STAGE_BYTES);
              bulk_load(sbuf, g_y + (size_t)(rb * 4 + ct) * 2560, STAGE_BYTES, c.bar(B_PREV));
            }
            __syncwarp();
          }
        }
      }
      if (c.warp == 2) {
        const long long t0 = clock64();
        while (clock64() - t0 < PF_W) __nanosleep(100);
        {
          const int ln = cta * 32 + c.lane;
          #pragma unroll 1
          for (int i = ln; i < 6400; i += 4096) { prefetch_l2(hre + (size_t)i * 64); prefetch_l2(him + (size_t)i * 64); }
          #pragma unroll 1
          for (int i = ln; i < 15360; i += 4096) prefetch_l2(win + (size_t)i * 64);
          #pragma unroll 1
          for (int i = ln; i < 7680; i += 4096) prefetch_l2(wout + (size_t)i * 64);
        }
        if (isG) {
          #pragma unroll 1
          for (int i = 0; i < 10; i++) {
            while (clock64() - t0 < PF_X + i * 1000) __nanosleep(100);
            prefetch_l2(x + (size_t)(row0 + ct * 32 + c.lane) * DM + i * 64);
          }
        }
      }
      if (c.warp == 1) {
        #pragma unroll 1
        for (int job = 0; job < (isG ? 5 : 2); job++) {
          mbar_wait(c.bar(B_STORE + (job & 1)), (job >> 1) & 1);
          if (elect_one()) {
            if (isG && job >= 3) {
              #pragma unroll
              for (int b = 0; b < 5; b++) tma_store(&maps.m[M_OUT], c.base + ((IT_Y + 1) & 3) * STAGE_BYTES + b * 8192 + (job - 3) * 4096, ct * 160 + b * 32, row0 + (job - 3) * 64, 1);
              bulk_commit();
              if (job == 4) bulk_wait_read();
            } else {
              const CUtensorMap* tm = &maps.m[isG ? (job == 2 ? M_HT : M_Z2NT) : M_ABT];
              const int c0 = row0 + (isG ? 0 : job * SEQ), rows = isG ? 192 : 160;
              tma_store(tm, sbuf, c0, ct * rows, !(isG && job == 1));
              tma_store(tm, sbuf + rows * 128, c0 + 64, ct * rows, !(isG && job == 0));
              bulk_commit();
              bulk_wait_read();
              if (!(isG && job == 0)) mbar_arrive(c.bar(B_SFREE + job - (isG ? 1 : 0)));
              if (!isG && job == 1) { mbar_arrive_cluster(c.bar(B_SFREE2), 0); mbar_arrive_cluster(c.bar(B_SFREE2), 1); }
              bulk_wait_all();
              flag_set(isG ? (job == 2 ? FL_H + rb * 4 + ct : FL_Z2N + (ct * 2 + job) * 16 + rb) : FL_AB + (job * 4 + ct) * 16 + rb, tag);
            }
          }
          __syncwarp();
        }
      }
    }
  } else {
    asm volatile("setmaxnreg.inc.sync.aligned.u32 232;");
    const uint32_t a0 = stage_t_addr(c);
    #pragma unroll 1
    for (int live = 0; live < 2; live++) {
      if (live) cp_async_wait();
      float v[40], sm = 0.f, sq = 0.f;
      #pragma unroll
      for (int i = 0; i < 5; i++) {
        const uint4 u = lds128u(xa + i * 256);
        v[8 * i] = bf_lo(u.x); v[8 * i + 1] = bf_hi(u.x); v[8 * i + 2] = bf_lo(u.y); v[8 * i + 3] = bf_hi(u.y);
        v[8 * i + 4] = bf_lo(u.z); v[8 * i + 5] = bf_hi(u.z); v[8 * i + 6] = bf_lo(u.w); v[8 * i + 7] = bf_hi(u.w);
      }
      #pragma unroll
      for (int i = 0; i < 40; i += 4) sm += (v[i] + v[i + 1]) + (v[i + 2] + v[i + 3]);
      #pragma unroll
      for (int o = 1; o < 16; o <<= 1) sm += __shfl_xor_sync(0xffffffffu, sm, o);
      const float mean = sm * (1.0f / DM);
      #pragma unroll
      for (int i = 0; i < 40; i += 2) { v[i] -= mean; v[i + 1] -= mean; sq += fmaf(v[i], v[i], v[i + 1] * v[i + 1]); }
      #pragma unroll
      for (int o = 1; o < 16; o <<= 1) sq += __shfl_xor_sync(0xffffffffu, sq, o);
      const float rstd = rsqrtf(sq * (1.0f / DM) + LN_EPS);
      #pragma unroll
      for (int i = 0; i < 5; i++)
        stg128(g_xn + (size_t)(xrow + (threadIdx.x >> 4)) * DM + (threadIdx.x & 15) * 8 + i * 128,
               make_uint4(pack_bf16(v[8 * i] * rstd, v[8 * i + 1] * rstd), pack_bf16(v[8 * i + 2] * rstd, v[8 * i + 3] * rstd),
                          pack_bf16(v[8 * i + 4] * rstd, v[8 * i + 5] * rstd), pack_bf16(v[8 * i + 6] * rstd, v[8 * i + 7] * rstd)), live);
      if (!live) cluster_wait();
      mbar_arrive_if(c.bar(B_XN), live);
    }
    auto staged = [&](int job, int live) { fence_async_smem(); mbar_arrive_if(c.bar(B_STORE + (job & 1)), live); };

    const int orow = c.warp * 16 + ((c.lane >> 3) & 1) * 8 + (c.lane & 7);
    const uint32_t o0 = orow * 64 + (((c.lane >> 4) ^ ((orow >> 1) & 3)) << 4);
    float acc[2][80];
    if (!isG) {
      auto epi_ab = [&](int job, uint32_t sgn, int live) {
        #pragma unroll
        for (int mb = 0; mb < 2; mb++) {
          if (live || c.warp == mb) {
            #pragma unroll
            for (int j = 0; j < 20; j += 2)
              stmatrix_x4_t(a0 + mb * (160 * 128) + j * 1024,
                            pack_bf16(acc[mb][4 * j + 0], acc[mb][4 * j + 1]) ^ sgn, pack_bf16(acc[mb][4 * j + 2], acc[mb][4 * j + 3]) ^ sgn,
                            pack_bf16(acc[mb][4 * j + 4], acc[mb][4 * j + 5]) ^ sgn, pack_bf16(acc[mb][4 * j + 6], acc[mb][4 * j + 7]) ^ sgn, live);
          }
        }
        staged(job, live);
      };
      if (wg == 0) {
        mainloop<160, 0, 0, true>(c, acc, 0, 10, false, c.bar(B_TURN1));
        drain<160>(c, acc, 9);
      }
      epi_ab(0, 0u, wg == 0);
      if (wg == 1) {
        mbar_wait(c.bar(B_TURN1), 0);
        mainloop<160, 0, 0, true>(c, acc, 10, 10, false, 0);
        drain<160>(c, acc, 19);
        mbar_wait(c.bar(B_SFREE), 0);
      }
      epi_ab(1, 0x80008000u, wg == 1);
      wgmma_fence();
      #pragma unroll 1
      for (int k = 0; k < (wg == (rb & 1) ? NY + YSOLO : NY); k++) {
        const int s = k & 3;
        mbar_wait(c.bar(B_FULL2 + s), (k >> 2) & 1);
        const uint32_t sa = c.base + s * STAGE2_BYTES;
        const uint64_t da = make_desc(sa + wg * 16384, 16, 1024, 1), db = make_desc(sa + 32768, 16, 1024, 1);
        wgmma_fence();
        #pragma unroll
        for (int kk = 0; kk < 4; kk++)
          #pragma unroll
          for (int mb = 0; mb < 2; mb++) Wgmma<160, 0, 0>::mma(acc[mb], da + (uint64_t)(mb * 512 + kk * 2), db + (uint64_t)(kk * 2), (k | kk) ? 1 : 0);
        wgmma_commit();
        if (k > 0) { wgmma_wait<1>(); if (c.lane < (k > NY ? 4 : 2)) mbar_arrive_cluster(c.bar(B_EMPTY2 + ((k - 1) & 3)), c.lane & 1); }
      }
      wgmma_wait<0>();
      fence_acc<160>(acc);
      if (wg != (rb & 1) && c.lane < 2) mbar_arrive_cluster(c.bar(B_EMPTY2 + ((NY - 1) & 3)), c.lane);
      named_sync(1 + wg, 128);
      #pragma unroll
      for (int i = 0; i < 20; i++) {
        const float* a = &acc[i / 10][(i % 10) * 8];
        sts128u(c.base + (i >> 3) * STAGE2_BYTES + wg * 16384 + (i & 7) * 2048 + tid * 16, pack_bf16(a[0], a[1]), pack_bf16(a[2], a[3]), pack_bf16(a[4], a[5]), pack_bf16(a[6], a[7]), 1);
      }
      fence_async_smem();
      named_sync(1 + wg, 128);
      if (c.warp == 0 && elect_one()) {
        const int part = wg == (rb & 1), rbo = (rb & ~1) + wg;
        #pragma unroll
        for (int i = 0; i < 3; i++)
          bulk_store(g_y + (size_t)(part * 64 + rbo * 4 + ct) * 2560 + i * 1024, c.base + i * STAGE2_BYTES + wg * 16384, i < 2 ? 16384 : 8192);
        bulk_commit();
        const unsigned tag = c.tag();
        bulk_wait_all();
        flag_set(FL_F + (rbo * 4 + ct) * 2 + part, tag);
      }
    } else {
      float acz[2][96];
      if (wg == 0) {
        mainloop<192, 0, 1, true>(c, acz, 0, 10, false, c.bar(B_TURN1));
        drain<192>(c, acz, 9);
      }
      {
        const int live = wg == 0;
        const unsigned tag = c.tag();
        u64* const zst = &g_z2stat[(row0 + c.warp * 16 + (c.lane >> 2)) * 2];
        float s0 = 0.f, s1 = 0.f, q0 = 0.f, q1 = 0.f;
        auto gelu_part = [&](auto mb_c, auto hf_c) {
          constexpr int mb = decltype(mb_c)::value, hf = decltype(hf_c)::value;
          if (live || c.warp == mb * 2 + hf) {
            #pragma unroll
            for (int j = hf * 12; j < hf * 12 + 12; j++) {
              const float g0 = gelu2(acz[mb][4 * j]), g1 = gelu2(acz[mb][4 * j + 1]);
              const float g2 = gelu2(acz[mb][4 * j + 2]), g3 = gelu2(acz[mb][4 * j + 3]);
              acz[mb][4 * j] = g0; acz[mb][4 * j + 1] = g1; acz[mb][4 * j + 2] = g2; acz[mb][4 * j + 3] = g3;
              s0 += g0 + g1; s1 += g2 + g3;
              q0 = fmaf(g0, g0, q0); q0 = fmaf(g1, g1, q0); q1 = fmaf(g2, g2, q1); q1 = fmaf(g3, g3, q1);
            }
          }
        };
        auto publish = [&](int mb) {
          const bool up = c.lane & 2;
          float sm = (up ? s1 : s0) + __shfl_xor_sync(0xffffffffu, up ? s0 : s1, 2);
          float sq = (up ? q1 : q0) + __shfl_xor_sync(0xffffffffu, up ? q0 : q1, 2);
          sm += __shfl_xor_sync(0xffffffffu, sm, 1); sq += __shfl_xor_sync(0xffffffffu, sq, 1);
          st_tag2(zst + (mb * 64 + (up ? 8 : 0)) * 2 + ct * (SEQ * 2), tagged(sm, tag), tagged(sq, tag), live && !(c.lane & 1));
          s0 = s1 = q0 = q1 = 0.f;
        };
        uint4 e0 = make_uint4(0, 0, 0, 0), e1 = e0;
        auto fetch = [&](int mb) {
          e0 = ld_tag2(zst + mb * 128 + (c.lane & 3) * (SEQ * 2), live); e1 = ld_tag2(zst + mb * 128 + 16 + (c.lane & 3) * (SEQ * 2), live);
        };
        auto norm_stage = [&](auto mb_c) {
          constexpr int mb = decltype(mb_c)::value;
          if (live || c.warp == mb * 2) {
            #pragma unroll 1
            for (int sp = 0; sp < SPIN_MAX; sp++) {
              const bool ok = e0.y == tag && e0.w == tag && e1.y == tag && e1.w == tag;
              if (__all_sync(0xffffffffu, ok) || !live) break;
              fetch(mb);
            }
            float m0 = __uint_as_float(e0.x), v0 = __uint_as_float(e0.z), m1 = __uint_as_float(e1.x), v1 = __uint_as_float(e1.z);
            #pragma unroll
            for (int o = 1; o < 4; o <<= 1) {
              m0 += __shfl_xor_sync(0xffffffffu, m0, o); v0 += __shfl_xor_sync(0xffffffffu, v0, o);
              m1 += __shfl_xor_sync(0xffffffffu, m1, o); v1 += __shfl_xor_sync(0xffffffffu, v1, o);
            }
            m0 *= 1.0f / FH; m1 *= 1.0f / FH;
            const float r0 = 0.5f * rsqrtf(fmaxf(v0 * (1.0f / FH) - m0 * m0, 0.f) + 4.0f * LN_EPS), r1 = 0.5f * rsqrtf(fmaxf(v1 * (1.0f / FH) - m1 * m1, 0.f) + 4.0f * LN_EPS);
            const float n0 = -m0 * r0, n1 = -m1 * r1;
            #pragma unroll
            for (int j = 0; j < 24; j += 2) {
              if (mb == 0 && j == 12) fetch(1);
              stmatrix_x4_t(a0 + mb * (192 * 128) + j * 1024,
                            pack_bf16(fmaf(acz[mb][4 * j + 0], r0, n0), fmaf(acz[mb][4 * j + 1], r0, n0)), pack_bf16(fmaf(acz[mb][4 * j + 2], r1, n1), fmaf(acz[mb][4 * j + 3], r1, n1)),
                            pack_bf16(fmaf(acz[mb][4 * j + 4], r0, n0), fmaf(acz[mb][4 * j + 5], r0, n0)), pack_bf16(fmaf(acz[mb][4 * j + 6], r1, n1), fmaf(acz[mb][4 * j + 7], r1, n1)), live);
            }
            staged(mb, live);
          }
        };
        gelu_part(IC<0>(), IC<0>());
        gelu_part(IC<0>(), IC<1>());
        publish(0);
        gelu_part(IC<1>(), IC<0>());
        fetch(0);
        gelu_part(IC<1>(), IC<1>());
        publish(1);
        norm_stage(IC<0>());
        norm_stage(IC<1>());
      }
      if (wg == 1) {
        mbar_wait(c.bar(B_TURN1), 0);
        mainloop<192, 0, 1, true>(c, acz, 10, 10, false, c.bar(B_TURN0));
        drain<192>(c, acz, 19);
        mbar_wait(c.bar(B_SFREE), 0);
        mbar_wait(c.bar(B_OWN), 0);
        #pragma unroll
        for (int mb = 0; mb < 2; mb++)
          #pragma unroll
          for (int j = 0; j < 24; j += 2)
            stmatrix_x4_t(a0 + mb * (192 * 128) + j * 1024,
                          pack_bf16(acz[mb][4 * j + 0], acz[mb][4 * j + 1]), pack_bf16(acz[mb][4 * j + 2], acz[mb][4 * j + 3]),
                          pack_bf16(acz[mb][4 * j + 4], acz[mb][4 * j + 5]), pack_bf16(acz[mb][4 * j + 6], acz[mb][4 * j + 7]), 1);
      } else {
        mbar_wait(c.bar(B_STORE), 0); mbar_wait(c.bar(B_STORE1), 0);
        mbar_wait(c.bar(B_TURN0), 0);
        first_bias<192>(c, acz);
        mainloop<192, 0, 0, false, 1, 2>(c, acz, 20, 32, false, c.bar(B_TURN1));
        drain<192>(c, acz, 51);
        mbar_wait(c.bar(B_Z1RDY), 0);
      }
      if (wg == 0 || c.warp == 0) {
        const int live = wg == 0;
        uint32_t gp[24][4], z[24][4];
        #pragma unroll
        for (int i = 0; i < 24; i++)
          #pragma unroll
          for (int e = 0; e < 4; e++) gp[i][e] = pack_bf16(acz[i / 12][(i % 12) * 8 + 2 * e], acz[i / 12][(i % 12) * 8 + 2 * e + 1]);
        #pragma unroll
        for (int i = 0; i < 24; i++) ldmatrix_x4_t(a0 + i * 2048, z[i], 1);
        #pragma unroll
        for (int i = 0; i < 24; i++)
          stmatrix_x4_t(a0 + i * 2048, mul_bf16x2(z[i][0], gp[i][0]), mul_bf16x2(z[i][1], gp[i][1]), mul_bf16x2(z[i][2], gp[i][2]), mul_bf16x2(z[i][3], gp[i][3]), live);
        staged(2, live);
      }
      if (wg == 1) {
        named_sync(2, 128);
        #pragma unroll 1
        for (int i = 0; i < 24; i += 3) {
          uint4 v3[3];
          #pragma unroll
          for (int k = 0; k < 3; k++) v3[k] = lds128u(sbuf + tid * 16 + (i + k) * 2048);
          #pragma unroll
          for (int k = 0; k < 3; k++) {
            uint32_t w[4] = {v3[k].x, v3[k].y, v3[k].z, v3[k].w};
            #pragma unroll
            for (int e = 0; e < 4; e++) w[e] = pack_bf16(gelu2(bf_lo(w[e])), gelu2(bf_hi(w[e])));
            sts128u(sbuf + tid * 16 + (i + k) * 2048, w[0], w[1], w[2], w[3], 1);
          }
        }
        mbar_arrive(c.bar(B_Z1RDY));
        mbar_wait(c.bar(B_TURN1), 1);
        mbar_wait(c.bar(B_TAB), 0);
        #pragma unroll
        for (int mb = 0; mb < 2; mb++) {
          const int it = 52 + mb, s = it & (STAGES - 1);
          mbar_wait(c.bar(B_FULL + s), (it / STAGES) & 1);
          const uint64_t da = make_desc(c.ext(X_ID), 16, 1024, 1), db = make_desc(c.base + s * STAGE_BYTES + A_BYTES, 8192, 1024, 1);
          wgmma_fence();
          Wgmma<160, 0, 1>::mma_first(acc[mb], da, db);
          #pragma unroll
          for (int kk = 1; kk < 4; kk++) Wgmma<160, 0, 1>::mma(acc[mb], da + (uint64_t)(kk * 2), db + (uint64_t)(kk * 128), 1);
          wgmma_commit();
          if (mb) { wgmma_wait<1>(); release_stage(c, 52); }
        }
        mainloop<160, 0, 0, false>(c, acc, IT_F, JSPLIT, true, 0);
        mbar_wait(c.bar(B_STORE), 1);
        mainloop<160, 1, 1, false, 2, 3>(c, acc, IT_F + JSPLIT, 12, true, 0);
        drain<160>(c, acc, IT_Y - 1);
        named_sync(2, 128);
        mbar_wait(c.bar(B_PREV), 0);
        mbar_wait(c.bar(B_FULL + (IT_Y & 3)), (IT_Y / STAGES) & 1);
      }
      if (wg == 1 || c.warp == 0) {
        const int live = wg == 1;
        const uint32_t y1 = c.base + (IT_Y & 3) * STAGE_BYTES + tid * 16, ob = c.base + ((IT_Y + 1) & 3) * STAGE_BYTES + o0;
        #pragma unroll
        for (int g = 0; g < 4; g++) {
          uint4 u[5], v[5];
          #pragma unroll
          for (int i = 0; i < 5; i++) { u[i] = lds128u(sbuf + tid * 16 + (g * 5 + i) * 2048); v[i] = lds128u(y1 + (g * 5 + i) * 2048); }
          #pragma unroll
          for (int i = 0; i < 5; i++) {
            const int j = (g & 1) * 5 + i;
            const float* a = &acc[g >> 1][j * 8];
            stmatrix_x4((ob ^ ((j & 1) << 5)) + (j >> 1) * 8192 + (g >> 1) * 4096,
                        add_bf16x2(add_bf16x2(u[i].x, v[i].x), pack_bf16(a[0], a[1])), add_bf16x2(add_bf16x2(u[i].y, v[i].y), pack_bf16(a[2], a[3])),
                        add_bf16x2(add_bf16x2(u[i].z, v[i].z), pack_bf16(a[4], a[5])), add_bf16x2(add_bf16x2(u[i].w, v[i].w), pack_bf16(a[6], a[7])), live);
          }
          if (g & 1) staged(3 + (g >> 1), live);
        }
      }
    }
  }
  __syncwarp();
  cluster_arrive();
  cluster_wait();
}

typedef CUresult (*EncodeFn)(CUtensorMap*, CUtensorMapDataType, cuuint32_t, void*, const cuuint64_t*, const cuuint64_t*,
                             const cuuint32_t*, const cuuint32_t*, CUtensorMapInterleave, CUtensorMapSwizzle,
                             CUtensorMapL2promotion, CUtensorMapFloatOOBfill);

void make_map(EncodeFn enc, CUtensorMap* m, const void* p, int rows, int cols, int box_rows, int box_cols, CUtensorMapSwizzle sw) {
  cuuint64_t gd[2] = {(cuuint64_t)cols, (cuuint64_t)rows};
  cuuint64_t gs[1] = {(cuuint64_t)cols * 2};
  cuuint32_t bd[2] = {(cuuint32_t)box_cols, (cuuint32_t)box_rows};
  cuuint32_t es[2] = {1, 1};
  enc(m, CU_TENSOR_MAP_DATA_TYPE_BFLOAT16, 2, (void*)p, gd, gs, bd, es, CU_TENSOR_MAP_INTERLEAVE_NONE, sw,
      CU_TENSOR_MAP_L2_PROMOTION_L2_128B, CU_TENSOR_MAP_FLOAT_OOB_FILL_NONE);
}

}

extern "C" void kernel_launch(void* const* d_in, const int* in_sizes, int n_in, void* d_out, int out_size) {
  const __nv_bfloat16* x = (const __nv_bfloat16*)d_in[0];
  const __nv_bfloat16* sre = (const __nv_bfloat16*)d_in[1];
  const __nv_bfloat16* sim = (const __nv_bfloat16*)d_in[2];
  const __nv_bfloat16* hre = (const __nv_bfloat16*)d_in[3];
  const __nv_bfloat16* him = (const __nv_bfloat16*)d_in[4];
  const __nv_bfloat16* win = (const __nv_bfloat16*)d_in[6];
  const __nv_bfloat16* wsp = (const __nv_bfloat16*)d_in[7];
  const __nv_bfloat16* bsp = (const __nv_bfloat16*)d_in[8];
  const __nv_bfloat16* wout = (const __nv_bfloat16*)d_in[9];

  void* fn = nullptr;
  cudaDriverEntryPointQueryResult qr;
  cudaGetDriverEntryPoint("cuTensorMapEncodeTiled", &fn, cudaEnableDefault, &qr);
  EncodeFn enc = (EncodeFn)fn;
  void *p_xn, *p_abT, *p_z2nT, *p_hT;
  cudaGetSymbolAddress(&p_xn, g_xn);
  cudaGetSymbolAddress(&p_abT, g_abT);
  cudaGetSymbolAddress(&p_z2nT, g_z2nT);
  cudaGetSymbolAddress(&p_hT, g_hT);
  Maps m;
  const CUtensorMapSwizzle S128 = CU_TENSOR_MAP_SWIZZLE_128B;
  make_map(enc, &m.m[M_X], p_xn, SEQ, DM, 64, 64, S128);
  make_map(enc, &m.m[M_HRE], hre, DM, DM, 160, 64, S128);
  make_map(enc, &m.m[M_HIM], him, DM, DM, 160, 64, S128);
  make_map(enc, &m.m[M_WIN], win, DM, 2 * FH, 64, 64, S128);
  make_map(enc, &m.m[M_SRE2], sre, SEQ, SEQ, 128, 64, S128);
  make_map(enc, &m.m[M_SIM2], sim, SEQ, SEQ, 128, 64, S128);
  make_map(enc, &m.m[M_SIM], sim, SEQ, SEQ, 64, 64, S128);
  make_map(enc, &m.m[M_WSP], wsp, SEQ, SEQ, 64, 64, S128);
  make_map(enc, &m.m[M_ABT], p_abT, DM, 2 * SEQ, 160, 64, S128);
  make_map(enc, &m.m[M_Z2NT], p_z2nT, FH, SEQ, 192, 64, S128);
  make_map(enc, &m.m[M_HT], p_hT, FH, SEQ, 192, 64, S128);
  make_map(enc, &m.m[M_HTLD], p_hT, FH, SEQ, 64, 64, S128);
  make_map(enc, &m.m[M_WOUT], wout, FH, DM, 64, 64, S128);
  make_map(enc, &m.m[M_OUT], d_out, SEQ, DM, 64, 32, CU_TENSOR_MAP_SWIZZLE_64B);
  make_map(enc, &m.m[M_XB], x, SEQ, DM, 64, 64, S128);
  cudaFuncSetAttribute(fused_kernel, cudaFuncAttributeMaxDynamicSharedMemorySize, SMEM_BYTES);
  fused_kernel<<<NCTA, 384, SMEM_BYTES>>>(m, x, hre, him, win, wout, bsp);
}
```

```cpp
#include <cuda.h>
#include <cuda_runtime.h>
#include <cuda_bf16.h>
#include <stdint.h>

extern __shared__ __align__(1024) uint8_t smem_raw[];

namespace {

constexpr int SEQ = 2048, DM = 640, FH = 768;
constexpr int STAGES = 4;
constexpr int STAGE_BYTES = 40960;
constexpr int A_BYTES = 16384;
constexpr int SBUF_OFF = STAGES * STAGE_BYTES;
constexpr int EXT_OFF = SBUF_OFF + 49152;
constexpr int X_ID = 0, X_A = 8192, X_Z = 10240, X_ONES = 12288, X_TAG = 12416, X_MASK = 12420;
constexpr int BAR_OFF = EXT_OFF + 12544;
constexpr int SMEM_BYTES = BAR_OFF + 512;
constexpr int JSPLIT = 4;
constexpr int YSOLO = 4;
static_assert((JSPLIT + YSOLO) % 2 == 0, "the two F-CTAs of a tile split K evenly");
constexpr int NY = 16 + (32 - JSPLIT - YSOLO) / 2;
constexpr int IT_F = 54;
constexpr int IT_Y = IT_F + JSPLIT + 12;
constexpr int STAGE2_BYTES = 32768 + 160 * 128;
constexpr int NCTA = 128;
constexpr float LN_EPS = 1e-5f;
static_assert(SMEM_BYTES <= 232448, "smem");

enum { M_X, M_HRE, M_HIM, M_WIN, M_SRE2, M_SIM2, M_SIM, M_WSP, M_ABT, M_Z2NT, M_HT, M_HTLD, M_WOUT, M_OUT, M_XB, M_COUNT };
struct Maps { CUtensorMap m[M_COUNT]; };

typedef unsigned long long u64;
__device__ __align__(1024) __nv_bfloat16 g_xn[SEQ * DM];
__device__ __align__(1024) uint4 g_y[2 * 64 * 2560];
__device__ __align__(1024) __nv_bfloat16 g_abT[DM * 2 * SEQ];
__device__ __align__(1024) __nv_bfloat16 g_z2nT[FH * SEQ];
__device__ __align__(1024) __nv_bfloat16 g_hT[FH * SEQ];
__device__ __align__(128) u64 g_z2stat[4 * SEQ * 2];
enum { FL_AB = 0, FL_Z2N = 128, FL_H = 256, FL_F = 320, FL_XN = 448, FL_COUNT = 576 };
__device__ __align__(128) unsigned g_flags[FL_COUNT * 16];
__device__ unsigned g_ticket;

__device__ __forceinline__ void mbar_init(uint32_t bar, uint32_t cnt) { asm volatile("mbarrier.init.shared::cta.b64 [%0], %1;" :: "r"(bar), "r"(cnt) : "memory"); }
__device__ __forceinline__ void mbar_expect_tx(uint32_t bar, uint32_t bytes) { asm volatile("mbarrier.arrive.expect_tx.shared::cta.b64 _, [%0], %1;" :: "r"(bar), "r"(bytes) : "memory"); }
__device__ __forceinline__ void mbar_arrive(uint32_t bar) { asm volatile("mbarrier.arrive.shared::cta.b64 _, [%0];" :: "r"(bar) : "memory"); }
__device__ __forceinline__ void mbar_arrive_if(uint32_t bar, int live) {
  asm volatile("{\n.reg .pred p;\nsetp.ne.b32 p, %1, 0;\n@p mbarrier.arrive.shared::cta.b64 _, [%0];\n}\n" :: "r"(bar), "r"(live) : "memory");
}
__device__ __forceinline__ void mbar_arrive_cluster(uint32_t bar, uint32_t cta) {
  asm volatile("{\n.reg .b32 ra;\nmapa.shared::cluster.u32 ra, %0, %1;\nmbarrier.arrive.shared::cluster.b64 _, [ra];\n}\n" :: "r"(bar), "r"(cta) : "memory");
}
__device__ __forceinline__ void mbar_wait(uint32_t bar, uint32_t parity) {
  asm volatile("{\n.reg .pred p;\n.reg .u32 c;\nmov.u32 c, 0;\nLAB_WAIT:\n"
               "mbarrier.try_wait.parity.shared::cta.b64 p, [%0], %1;\n@p bra LAB_DONE;\n"
               "add.u32 c, c, 1;\nsetp.lt.u32 p, c, 20000;\n@p bra LAB_WAIT;\nLAB_DONE:\n}\n" :: "r"(bar), "r"(parity) : "memory");
}
__device__ __forceinline__ void tma_load(uint32_t dst, const CUtensorMap* tm, uint32_t bar, int c0, int c1) {
  asm volatile("cp.async.bulk.tensor.2d.shared::cluster.global.mbarrier::complete_tx::bytes [%0], [%1, {%3, %4}], [%2];"
    :: "r"(dst), "l"((uint64_t)tm), "r"(bar), "r"(c0), "r"(c1) : "memory");
}
__device__ __forceinline__ void tma_load_mc(uint32_t dst, const CUtensorMap* tm, uint32_t bar, int c0, int c1, uint64_t policy) {
  asm volatile("cp.async.bulk.tensor.2d.shared::cluster.global.mbarrier::complete_tx::bytes.multicast::cluster.L2::cache_hint [%0], [%1, {%3, %4}], [%2], %5, %6;"
    :: "r"(dst), "l"((uint64_t)tm), "r"(bar), "r"(c0), "r"(c1), "h"((uint16_t)3), "l"(policy) : "memory");
}
__device__ __forceinline__ void bulk_load(uint32_t dst, const void* src, uint32_t bytes, uint32_t bar) {
  asm volatile("cp.async.bulk.shared::cluster.global.mbarrier::complete_tx::bytes [%0], [%1], %2, [%3];"
    :: "r"(dst), "l"((uint64_t)src), "r"(bytes), "r"(bar) : "memory");
}
__device__ __forceinline__ void tma_store(const CUtensorMap* tm, uint32_t src, int c0, int c1, int live) {
  asm volatile("{\n.reg .pred p;\nsetp.ne.b32 p, %4, 0;\n@p cp.async.bulk.tensor.2d.global.shared::cta.bulk_group [%0, {%2, %3}], [%1];\n}\n"
    :: "l"((uint64_t)tm), "r"(src), "r"(c0), "r"(c1), "r"(live) : "memory");
}
__device__ __forceinline__ void bulk_store(void* dst, uint32_t src, uint32_t bytes) {
  asm volatile("cp.async.bulk.global.shared::cta.bulk_group [%0], [%1], %2;" :: "l"(dst), "r"(src), "r"(bytes) : "memory");
}
__device__ __forceinline__ void bulk_commit() { asm volatile("cp.async.bulk.commit_group;" ::: "memory"); }
__device__ __forceinline__ void bulk_wait_read() { asm volatile("cp.async.bulk.wait_group.read 0;" ::: "memory"); }
__device__ __forceinline__ void bulk_wait_all() { asm volatile("cp.async.bulk.wait_group 0;" ::: "memory"); }
__device__ __forceinline__ void cp_async16(uint32_t dst, const void* src) {
  asm volatile("cp.async.cg.shared.global [%0], [%1], 16;" :: "r"(dst), "l"(src) : "memory");
}
__device__ __forceinline__ void cp_async_wait() { asm volatile("cp.async.wait_all;" ::: "memory"); }
__device__ __forceinline__ void prefetch_l2(const void* p) { asm volatile("prefetch.global.L2 [%0];" :: "l"(p)); }
__device__ __forceinline__ void prefetch_tmap(const CUtensorMap* tm) { asm volatile("prefetch.tensormap [%0];" :: "l"((uint64_t)tm) : "memory"); }
__device__ __forceinline__ void fence_async_smem() { asm volatile("fence.proxy.async.shared::cta;" ::: "memory"); }
__device__ __forceinline__ void fence_async_global() { asm volatile("fence.proxy.async.global;" ::: "memory"); }
__device__ __forceinline__ void wgmma_fence() { asm volatile("wgmma.fence.sync.aligned;" ::: "memory"); }
__device__ __forceinline__ void wgmma_commit() { asm volatile("wgmma.commit_group.sync.aligned;" ::: "memory"); }
template<int N> __device__ __forceinline__ void wgmma_wait() { asm volatile("wgmma.wait_group.sync.aligned %0;" :: "n"(N) : "memory"); }
__device__ __forceinline__ void cluster_arrive() { asm volatile("barrier.cluster.arrive.relaxed.aligned;" ::: "memory"); }
__device__ __forceinline__ void cluster_wait() { asm volatile("barrier.cluster.wait.acquire.aligned;" ::: "memory"); }
__device__ __forceinline__ bool elect_one() {
  uint32_t p; asm volatile("{\n.reg .pred p;\nelect.sync _|p, 0xffffffff;\nselp.u32 %0, 1, 0, p;\n}\n" : "=r"(p)); return p;
}
__device__ __forceinline__ void named_sync(int id, int n) { asm volatile("bar.sync %0, %1;" :: "r"(id), "r"(n) : "memory"); }
__device__ __forceinline__ void stmatrix_x4(uint32_t addr, uint32_t r0, uint32_t r1, uint32_t r2, uint32_t r3, int live) {
  asm volatile("{\n.reg .pred p;\nsetp.ne.b32 p, %5, 0;\n@p stmatrix.sync.aligned.m8n8.x4.shared.b16 [%0], {%1, %2, %3, %4};\n}\n"
    :: "r"(addr), "r"(r0), "r"(r1), "r"(r2), "r"(r3), "r"(live) : "memory");
}
__device__ __forceinline__ void stmatrix_x4_t(uint32_t addr, uint32_t r0, uint32_t r1, uint32_t r2, uint32_t r3, int live) {
  asm volatile("{\n.reg .pred p;\nsetp.ne.b32 p, %5, 0;\n@p stmatrix.sync.aligned.m8n8.x4.trans.shared.b16 [%0], {%1, %2, %3, %4};\n}\n"
    :: "r"(addr), "r"(r0), "r"(r1), "r"(r2), "r"(r3), "r"(live) : "memory");
}
__device__ __forceinline__ void ldmatrix_x4_t(uint32_t addr, uint32_t (&r)[4], int live) {
  asm volatile("{\n.reg .pred p;\nsetp.ne.b32 p, %5, 0;\n@p ldmatrix.sync.aligned.m8n8.x4.trans.shared.b16 {%0, %1, %2, %3}, [%4];\n}\n"
    : "=r"(r[0]), "=r"(r[1]), "=r"(r[2]), "=r"(r[3]) : "r"(addr), "r"(live) : "memory");
}
__device__ __forceinline__ void sts128u(uint32_t addr, uint32_t a, uint32_t b, uint32_t c, uint32_t d, int live) {
  asm volatile("{\n.reg .pred p;\nsetp.ne.b32 p, %5, 0;\n@p st.shared.v4.b32 [%0], {%1, %2, %3, %4};\n}\n" :: "r"(addr), "r"(a), "r"(b), "r"(c), "r"(d), "r"(live) : "memory");
}
__device__ __forceinline__ uint4 lds128u(uint32_t addr) {
  uint4 v; asm volatile("ld.shared.v4.u32 {%0, %1, %2, %3}, [%4];" : "=r"(v.x), "=r"(v.y), "=r"(v.z), "=r"(v.w) : "r"(addr) : "memory"); return v;
}
__device__ __forceinline__ void sts32(uint32_t addr, float a) { asm volatile("st.shared.f32 [%0], %1;" :: "r"(addr), "f"(a) : "memory"); }
__device__ __forceinline__ float lds32(uint32_t addr) { float v; asm volatile("ld.shared.f32 %0, [%1];" : "=f"(v) : "r"(addr) : "memory"); return v; }
__device__ __forceinline__ uint32_t pack_bf16(float lo, float hi) {
  uint32_t r; asm("cvt.rn.bf16x2.f32 %0, %1, %2;" : "=r"(r) : "f"(hi), "f"(lo)); return r;
}
__device__ __forceinline__ uint32_t mul_bf16x2(uint32_t a, uint32_t b) {
  uint32_t r; asm("mul.rn.bf16x2 %0, %1, %2;" : "=r"(r) : "r"(a), "r"(b)); return r;
}
__device__ __forceinline__ uint32_t add_bf16x2(uint32_t a, uint32_t b) {
  uint32_t r; asm("add.rn.bf16x2 %0, %1, %2;" : "=r"(r) : "r"(a), "r"(b)); return r;
}
__device__ __forceinline__ float bf_lo(uint32_t v) { return __uint_as_float(v << 16); }
__device__ __forceinline__ float bf_hi(uint32_t v) { return __uint_as_float(v & 0xffff0000u); }

__device__ __forceinline__ u64 tagged(float v, unsigned tag) { return ((u64)tag << 32) | __float_as_uint(v); }
__device__ __forceinline__ void st_tag2(u64* p, u64 a, u64 b, int live) {
  asm volatile("{\n.reg .pred p;\nsetp.ne.b32 p, %3, 0;\n@p st.relaxed.gpu.global.v2.b64 [%0], {%1, %2};\n}\n" :: "l"(p), "l"(a), "l"(b), "r"(live) : "memory");
}
__device__ __forceinline__ uint4 ld_tag2(const u64* p, int live) {
  u64 a = 0, b = 0;
  asm volatile("{\n.reg .pred p;\nsetp.ne.b32 p, %3, 0;\n@p ld.relaxed.gpu.global.v2.b64 {%0, %1}, [%2];\n}\n" : "+l"(a), "+l"(b) : "l"(p), "r"(live) : "memory");
  return make_uint4((uint32_t)a, (uint32_t)(a >> 32), (uint32_t)b, (uint32_t)(b >> 32));
}
__device__ __forceinline__ void flag_set(int id, unsigned tag) {
  asm volatile("fence.proxy.async.global;\nfence.acq_rel.gpu;\nst.relaxed.gpu.global.u32 [%0], %1;" :: "l"(g_flags + id * 16), "r"(tag) : "memory");
}
__device__ __forceinline__ unsigned flag_get(int id) {
  unsigned v;
  asm volatile("ld.acquire.gpu.global.u32 %0, [%1];" : "=r"(v) : "l"(g_flags + id * 16) : "memory"); return v;
}
constexpr int SPIN_MAX = 2000000;
constexpr int PF_W = 2500, PF_X = 34000;

__device__ __forceinline__ float gelu2(float v) {
  const float K1 = 0.7978845608f, K2 = 0.7978845608f * 0.044715f;
  float a = v * fmaf(v * v, K2, K1);
  float t; asm("tanh.approx.f32 %0, %1;" : "=f"(t) : "f"(a));
  return fmaf(v, t, v);
}

template<int N, int TA, int TB> struct Wgmma;
template<int TA, int TB> struct Wgmma<160, TA, TB> {
  static __device__ __forceinline__ void mma(float (&d)[80], uint64_t da, uint64_t db, int scale_d) {
    asm volatile("{\n.reg .pred p;\nsetp.ne.b32 p, %82, 0;\n"
      "wgmma.mma_async.sync.aligned.m64n160k16.f32.bf16.bf16 {%0, %1, %2, %3, %4, %5, %6, %7, %8, %9, %10, %11, %12, %13, %14, %15, %16, %17, %18, %19, %20, %21, %22, %23, %24, %25, %26, %27, %28, %29, %30, %31, %32, %33, %34, %35, %36, %37, %38, %39, %40, %41, %42, %43, %44, %45, %46, %47, %48, %49, %50, %51, %52, %53, %54, %55, %56, %57, %58, %59, %60, %61, %62, %63, %64, %65, %66, %67, %68, %69, %70, %71, %72, %73, %74, %75, %76, %77, %78, %79}, %80, %81, p, 1, 1, %83, %84;\n}\n"
      : "+f"(d[0]), "+f"(d[1]), "+f"(d[2]), "+f"(d[3]), "+f"(d[4]), "+f"(d[5]), "+f"(d[6]), "+f"(d[7]), "+f"(d[8]), "+f"(d[9]), "+f"(d[10]), "+f"(d[11]), "+f"(d[12]), "+f"(d[13]), "+f"(d[14]), "+f"(d[15]), "+f"(d[16]), "+f"(d[17]), "+f"(d[18]), "+f"(d[19]), "+f"(d[20]), "+f"(d[21]), "+f"(d[22]), "+f"(d[23]), "+f"(d[24]), "+f"(d[25]), "+f"(d[26]), "+f"(d[27]), "+f"(d[28]), "+f"(d[29]), "+f"(d[30]), "+f"(d[31]), "+f"(d[32]), "+f"(d[33]), "+f"(d[34]), "+f"(d[35]), "+f"(d[36]), "+f"(d[37]), "+f"(d[38]), "+f"(d[39]), "+f"(d[40]), "+f"(d[41]), "+f"(d[42]), "+f"(d[43]), "+f"(d[44]), "+f"(d[45]), "+f"(d[46]), "+f"(d[47]), "+f"(d[48]), "+f"(d[49]), "+f"(d[50]), "+f"(d[51]), "+f"(d[52]), "+f"(d[53]), "+f"(d[54]), "+f"(d[55]), "+f"(d[56]), "+f"(d[57]), "+f"(d[58]), "+f"(d[59]), "+f"(d[60]), "+f"(d[61]), "+f"(d[62]), "+f"(d[63]), "+f"(d[64]), "+f"(d[65]), "+f"(d[66]), "+f"(d[67]), "+f"(d[68]), "+f"(d[69]), "+f"(d[70]), "+f"(d[71]), "+f"(d[72]), "+f"(d[73]), "+f"(d[74]), "+f"(d[75]), "+f"(d[76]), "+f"(d[77]), "+f"(d[78]), "+f"(d[79])
      : "l"(da), "l"(db), "r"(scale_d), "n"(TA), "n"(TB));
  }
  static __device__ __forceinline__ void mma_first(float (&d)[80], uint64_t da, uint64_t db) {
    asm volatile("{\n.reg .pred p;\nsetp.ne.b32 p, 0, 0;\n"
      "wgmma.mma_async.sync.aligned.m64n160k16.f32.bf16.bf16 {%0, %1, %2, %3, %4, %5, %6, %7, %8, %9, %10, %11, %12, %13, %14, %15, %16, %17, %18, %19, %20, %21, %22, %23, %24, %25, %26, %27, %28, %29, %30, %31, %32, %33, %34, %35, %36, %37, %38, %39, %40, %41, %42, %43, %44, %45, %46, %47, %48, %49, %50, %51, %52, %53, %54, %55, %56, %57, %58, %59, %60, %61, %62, %63, %64, %65, %66, %67, %68, %69, %70, %71, %72, %73, %74, %75, %76, %77, %78, %79}, %80, %81, p, 1, 1, %82, %83;\n}\n"
      : "=f"(d[0]), "=f"(d[1]), "=f"(d[2]), "=f"(d[3]), "=f"(d[4]), "=f"(d[5]), "=f"(d[6]), "=f"(d[7]), "=f"(d[8]), "=f"(d[9]), "=f"(d[10]), "=f"(d[11]), "=f"(d[12]), "=f"(d[13]), "=f"(d[14]), "=f"(d[15]), "=f"(d[16]), "=f"(d[17]), "=f"(d[18]), "=f"(d[19]), "=f"(d[20]), "=f"(d[21]), "=f"(d[22]), "=f"(d[23]), "=f"(d[24]), "=f"(d[25]), "=f"(d[26]), "=f"(d[27]), "=f"(d[28]), "=f"(d[29]), "=f"(d[30]), "=f"(d[31]), "=f"(d[32]), "=f"(d[33]), "=f"(d[34]), "=f"(d[35]), "=f"(d[36]), "=f"(d[37]), "=f"(d[38]), "=f"(d[39]), "=f"(d[40]), "=f"(d[41]), "=f"(d[42]), "=f"(d[43]), "=f"(d[44]), "=f"(d[45]), "=f"(d[46]), "=f"(d[47]), "=f"(d[48]), "=f"(d[49]), "=f"(d[50]), "=f"(d[51]), "=f"(d[52]), "=f"(d[53]), "=f"(d[54]), "=f"(d[55]), "=f"(d[56]), "=f"(d[57]), "=f"(d[58]), "=f"(d[59]), "=f"(d[60]), "=f"(d[61]), "=f"(d[62]), "=f"(d[63]), "=f"(d[64]), "=f"(d[65]), "=f"(d[66]), "=f"(d[67]), "=f"(d[68]), "=f"(d[69]), "=f"(d[70]), "=f"(d[71]), "=f"(d[72]), "=f"(d[73]), "=f"(d[74]), "=f"(d[75]), "=f"(d[76]), "=f"(d[77]), "=f"(d[78]), "=f"(d[79])
      : "l"(da), "l"(db), "n"(TA), "n"(TB));
  }
};
template<int TA, int TB> struct Wgmma<192, TA, TB> {
  static __device__ __forceinline__ void mma(float (&d)[96], uint64_t da, uint64_t db, int scale_d) {
    asm volatile("{\n.reg .pred p;\nsetp.ne.b32 p, %98, 0;\n"
      "wgmma.mma_async.sync.aligned.m64n192k16.f32.bf16.bf16 {%0, %1, %2, %3, %4, %5, %6, %7, %8, %9, %10, %11, %12, %13, %14, %15, %16, %17, %18, %19, %20, %21, %22, %23, %24, %25, %26, %27, %28, %29, %30, %31, %32, %33, %34, %35, %36, %37, %38, %39, %40, %41, %42, %43, %44, %45, %46, %47, %48, %49, %50, %51, %52, %53, %54, %55, %56, %57, %58, %59, %60, %61, %62, %63, %64, %65, %66, %67, %68, %69, %70, %71, %72, %73, %74, %75, %76, %77, %78, %79, %80, %81, %82, %83, %84, %85, %86, %87, %88, %89, %90, %91, %92, %93, %94, %95}, %96, %97, p, 1, 1, %99, %100;\n}\n"
      : "+f"(d[0]), "+f"(d[1]), "+f"(d[2]), "+f"(d[3]), "+f"(d[4]), "+f"(d[5]), "+f"(d[6]), "+f"(d[7]), "+f"(d[8]), "+f"(d[9]), "+f"(d[10]), "+f"(d[11]), "+f"(d[12]), "+f"(d[13]), "+f"(d[14]), "+f"(d[15]), "+f"(d[16]), "+f"(d[17]), "+f"(d[18]), "+f"(d[19]), "+f"(d[20]), "+f"(d[21]), "+f"(d[22]), "+f"(d[23]), "+f"(d[24]), "+f"(d[25]), "+f"(d[26]), "+f"(d[27]), "+f"(d[28]), "+f"(d[29]), "+f"(d[30]), "+f"(d[31]), "+f"(d[32]), "+f"(d[33]), "+f"(d[34]), "+f"(d[35]), "+f"(d[36]), "+f"(d[37]), "+f"(d[38]), "+f"(d[39]), "+f"(d[40]), "+f"(d[41]), "+f"(d[42]), "+f"(d[43]), "+f"(d[44]), "+f"(d[45]), "+f"(d[46]), "+f"(d[47]), "+f"(d[48]), "+f"(d[49]), "+f"(d[50]), "+f"(d[51]), "+f"(d[52]), "+f"(d[53]), "+f"(d[54]), "+f"(d[55]), "+f"(d[56]), "+f"(d[57]), "+f"(d[58]), "+f"(d[59]), "+f"(d[60]), "+f"(d[61]), "+f"(d[62]), "+f"(d[63]), "+f"(d[64]), "+f"(d[65]), "+f"(d[66]), "+f"(d[67]), "+f"(d[68]), "+f"(d[69]), "+f"(d[70]), "+f"(d[71]), "+f"(d[72]), "+f"(d[73]), "+f"(d[74]), "+f"(d[75]), "+f"(d[76]), "+f"(d[77]), "+f"(d[78]), "+f"(d[79]), "+f"(d[80]), "+f"(d[81]), "+f"(d[82]), "+f"(d[83]), "+f"(d[84]), "+f"(d[85]), "+f"(d[86]), "+f"(d[87]), "+f"(d[88]), "+f"(d[89]), "+f"(d[90]), "+f"(d[91]), "+f"(d[92]), "+f"(d[93]), "+f"(d[94]), "+f"(d[95])
      : "l"(da), "l"(db), "r"(scale_d), "n"(TA), "n"(TB));
  }
  static __device__ __forceinline__ void mma_first(float (&d)[96], uint64_t da, uint64_t db) {
    asm volatile("{\n.reg .pred p;\nsetp.ne.b32 p, 0, 0;\n"
      "wgmma.mma_async.sync.aligned.m64n192k16.f32.bf16.bf16 {%0, %1, %2, %3, %4, %5, %6, %7, %8, %9, %10, %11, %12, %13, %14, %15, %16, %17, %18, %19, %20, %21, %22, %23, %24, %25, %26, %27, %28, %29, %30, %31, %32, %33, %34, %35, %36, %37, %38, %39, %40, %41, %42, %43, %44, %45, %46, %47, %48, %49, %50, %51, %52, %53, %54, %55, %56, %57, %58, %59, %60, %61, %62, %63, %64, %65, %66, %67, %68, %69, %70, %71, %72, %73, %74, %75, %76, %77, %78, %79, %80, %81, %82, %83, %84, %85, %86, %87, %88, %89, %90, %91, %92, %93, %94, %95}, %96, %97, p, 1, 1, %98, %99;\n}\n"
      : "=f"(d[0]), "=f"(d[1]), "=f"(d[2]), "=f"(d[3]), "=f"(d[4]), "=f"(d[5]), "=f"(d[6]), "=f"(d[7]), "=f"(d[8]), "=f"(d[9]), "=f"(d[10]), "=f"(d[11]), "=f"(d[12]), "=f"(d[13]), "=f"(d[14]), "=f"(d[15]), "=f"(d[16]), "=f"(d[17]), "=f"(d[18]), "=f"(d[19]), "=f"(d[20]), "=f"(d[21]), "=f"(d[22]), "=f"(d[23]), "=f"(d[24]), "=f"(d[25]), "=f"(d[26]), "=f"(d[27]), "=f"(d[28]), "=f"(d[29]), "=f"(d[30]), "=f"(d[31]), "=f"(d[32]), "=f"(d[33]), "=f"(d[34]), "=f"(d[35]), "=f"(d[36]), "=f"(d[37]), "=f"(d[38]), "=f"(d[39]), "=f"(d[40]), "=f"(d[41]), "=f"(d[42]), "=f"(d[43]), "=f"(d[44]), "=f"(d[45]), "=f"(d[46]), "=f"(d[47]), "=f"(d[48]), "=f"(d[49]), "=f"(d[50]), "=f"(d[51]), "=f"(d[52]), "=f"(d[53]), "=f"(d[54]), "=f"(d[55]), "=f"(d[56]), "=f"(d[57]), "=f"(d[58]), "=f"(d[59]), "=f"(d[60]), "=f"(d[61]), "=f"(d[62]), "=f"(d[63]), "=f"(d[64]), "=f"(d[65]), "=f"(d[66]), "=f"(d[67]), "=f"(d[68]), "=f"(d[69]), "=f"(d[70]), "=f"(d[71]), "=f"(d[72]), "=f"(d[73]), "=f"(d[74]), "=f"(d[75]), "=f"(d[76]), "=f"(d[77]), "=f"(d[78]), "=f"(d[79]), "=f"(d[80]), "=f"(d[81]), "=f"(d[82]), "=f"(d[83]), "=f"(d[84]), "=f"(d[85]), "=f"(d[86]), "=f"(d[87]), "=f"(d[88]), "=f"(d[89]), "=f"(d[90]), "=f"(d[91]), "=f"(d[92]), "=f"(d[93]), "=f"(d[94]), "=f"(d[95])
      : "l"(da), "l"(db), "n"(TA), "n"(TB));
  }
};


__device__ __forceinline__ uint64_t make_desc(uint32_t addr, uint32_t lbo, uint32_t sbo, uint32_t swz) {
  return (uint64_t)((addr & 0x3FFFF) >> 4) | ((uint64_t)(lbo >> 4) << 16) | ((uint64_t)(sbo >> 4) << 32) | ((uint64_t)swz << 62);
}

enum { B_FULL = 0, B_EMPTY = STAGES, B_SFREE = 2 * STAGES, B_SFREE1, B_Z1RDY, B_TURN0, B_TURN1, B_TAB, B_OWN, B_OWN1, B_PREV, B_TAG, B_STORE, B_STORE1, B_XN, B_SFREE2, B_FULL2, B_EMPTY2 = B_FULL2 + 4, B_DEP = B_EMPTY2 + 4, B_COUNT = B_DEP + 8 };

template<int V> struct IC { static constexpr int value = V; };
struct Ctx {
  uint32_t base;
  int warp, lane;
  __device__ __forceinline__ uint32_t bar(int i) const { return base + BAR_OFF + 8 * i; }
  __device__ __forceinline__ uint32_t ext(int off) const { return base + EXT_OFF + off; }
  __device__ __forceinline__ unsigned tag() const { mbar_wait(bar(B_TAG), 0); return __float_as_uint(lds32(ext(X_TAG))); }
};

__device__ __forceinline__ void release_stage(const Ctx& c, int it) {
  if (c.lane < 2) mbar_arrive_cluster(c.bar(B_EMPTY + (it & (STAGES - 1))), c.lane);
}

template<int N, int TA, int TB, bool ZI, int OWN = 0, int NOWN = 0>
__device__ __forceinline__ void mainloop(const Ctx& c, float (&acc)[2][N / 2], int it0, int n, bool pend, uint32_t pass_bar) {
  wgmma_fence();
  #pragma unroll 1
  for (int k = 0; k < n; k++) {
    int it = it0 + k, s = it & (STAGES - 1);
    mbar_wait(c.bar(B_FULL + s), (it / STAGES) & 1);
    if (pass_bar && k == n - 1 && c.lane == 0 && c.warp == 0) mbar_arrive(pass_bar);
    uint32_t sa = c.base + s * STAGE_BYTES, sb = sa + A_BYTES, mstep = 512;
    if (OWN == 1 && k < NOWN) sb = c.base + SBUF_OFF + k * (192 * 128);
    if (OWN == 2 && k < NOWN) { sa = c.base + SBUF_OFF + k * 8192; mstep = 192 * 128 / 16; }
    uint64_t da = make_desc(sa, TA == 0 ? 16 : 8192, 1024, 1);
    uint64_t db = make_desc(sb, TB == 0 ? 16 : 8192, 1024, 1);
    wgmma_fence();
    #pragma unroll
    for (int kk = 0; kk < 4; kk++) {
      int sd = (ZI && k == 0 && kk == 0) ? 0 : 1;
      #pragma unroll
      for (int mb = 0; mb < 2; mb++)
        Wgmma<N, TA, TB>::mma(acc[mb], da + (uint64_t)(mb * mstep + (TA == 0 ? kk * 2 : kk * 128)), db + (uint64_t)(TB == 0 ? kk * 2 : kk * 128), sd);
    }
    wgmma_commit();
    wgmma_wait<1>();
    if (k > 0 || pend) release_stage(c, it - 1);
    if (OWN && k == NOWN && c.lane == 0) mbar_arrive(c.bar(B_OWN + OWN - 1));
  }
}
template<int N>
__device__ __forceinline__ void fence_acc(float (&acc)[2][N / 2]) {
  #pragma unroll
  for (int mb = 0; mb < 2; mb++)
    #pragma unroll
    for (int e = 0; e < N / 2; e++) asm volatile("" : "+f"(acc[mb][e]) :: "memory");
}
template<int N>
__device__ __forceinline__ void drain(const Ctx& c, float (&acc)[2][N / 2], int it_last) {
  wgmma_wait<0>();
  fence_acc<N>(acc);
  release_stage(c, it_last);
}
template<int N>
__device__ __forceinline__ void first_bias(const Ctx& c, float (&acc)[2][N / 2]) {
  mbar_wait(c.bar(B_TAB), 0);
  uint64_t da = make_desc(c.ext(X_A), 2048, 128, 0), db = make_desc(c.ext(X_ONES), 0, 0, 0);
  wgmma_fence();
  Wgmma<N, 0, 0>::mma_first(acc[0], da, db);
  Wgmma<N, 0, 0>::mma_first(acc[1], da + 64, db);
  wgmma_commit();
}

__device__ __forceinline__ uint32_t stage_t_addr(const Ctx& c) {
  int mi = c.lane >> 3, r = c.lane & 7;
  return c.base + SBUF_OFF + ((mi >> 1) * 8 + r) * 128 + (((2 * c.warp + (mi & 1)) ^ r) << 4);
}

__global__ void __cluster_dims__(2, 1, 1) __launch_bounds__(384, 1)
fused_kernel(const __grid_constant__ Maps maps, const __nv_bfloat16* __restrict__ x, const __nv_bfloat16* __restrict__ hre,
             const __nv_bfloat16* __restrict__ him, const __nv_bfloat16* __restrict__ win, const __nv_bfloat16* __restrict__ wout,
             const __nv_bfloat16* __restrict__ bsp) {
  Ctx c;
  asm("mov.u32 %0, smem_raw;" : "=r"(c.base));
  if (threadIdx.x == 1023) smem_raw[0] = 0;
  const int wg = __shfl_sync(0xffffffffu, threadIdx.x >> 7, 0), tid = threadIdx.x & 127;
  c.warp = __shfl_sync(0xffffffffu, tid >> 5, 0); c.lane = tid & 31;
  const int cta = blockIdx.x, rank = cta & 1, pair = cta >> 1;
  const bool isG = (pair >> 3) & 1;
  const int q = (pair >> 4) * 8 + (pair & 7), rb = q >> 1, ct = (q & 1) * 2 + rank;
  const int row0 = rb * 128;
  const uint32_t sbuf = c.base + SBUF_OFF;

  const int xrow = row0 + ((isG ? 4 : 0) + ct) * 16;
  const uint32_t xa = sbuf + (threadIdx.x >> 4) * 1280 + (threadIdx.x & 15) * 16;
  if (wg < 2) {
    #pragma unroll
    for (int i = 0; i < 5; i++) cp_async16(xa + i * 256, x + (size_t)(xrow + (threadIdx.x >> 4)) * DM + (threadIdx.x & 15) * 8 + i * 128);
  }
  if (threadIdx.x == 256) {
    #pragma unroll
    for (int s = 0; s < B_COUNT; s++)
      mbar_init(c.bar(s), (s >= B_EMPTY && s < B_EMPTY + STAGES) ? 8 : (s == B_Z1RDY || s == B_STORE || s == B_STORE1) ? 128 : s == B_TAB ? 32 : (s == B_OWN || s == B_OWN1) ? 4 : s == B_XN ? 256 : (s >= B_EMPTY2 && s < B_EMPTY2 + 4) ? 16 : s == B_SFREE2 ? 2 : 1);
    asm volatile("fence.mbarrier_init.release.cluster;" ::: "memory");
  } else if (threadIdx.x >= 288 && threadIdx.x < 288 + M_COUNT) {
    prefetch_tmap(&maps.m[threadIdx.x - 288]);
  }
  __syncwarp();
  cluster_arrive();

  if (wg == 2) {
    asm volatile("setmaxnreg.dec.sync.aligned.u32 40;");
    if (c.warp == 0) {
      int it = 0;
      uint64_t pol_stream, pol_normal;
      asm("createpolicy.fractional.L2::evict_normal.b64 %0, 1.0;" : "=l"(pol_normal));
      asm("createpolicy.fractional.L2::evict_first.b64 %0, 1.0;" : "=l"(pol_stream));
      auto wait_dep = [&](int d) {
        mbar_wait(c.bar(B_DEP + d), 0);
        fence_async_global();
      };
      auto wait_box = [&](int r) {
        #pragma unroll 1
        for (int sp = 0; sp < SPIN_MAX; sp++) {
          unsigned m; asm volatile("ld.acquire.cta.shared.u32 %0, [%1];" : "=r"(m) : "r"(c.ext(X_MASK)) : "memory");
          if ((m >> r) & 1) break;
        }
        fence_async_global();
      };
      auto run = [&](auto mode_c, const CUtensorMap* ma, const CUtensorMap* mb, int ka, int kb, int ks, int skip, int k0, int n, int nb0, uint32_t bytes, int fl) {
        constexpr int MODE = decltype(mode_c)::value;
        #pragma unroll 1
        for (int k = k0; k < n; k++, it++) {
          const int s = it & (STAGES - 1), ko = (k + (k >= skip ? 1 : 0)) * ks;
          const uint32_t sa = c.base + s * STAGE_BYTES, fb = c.bar(B_FULL + s);
          mbar_wait(c.bar(B_EMPTY + s), ((it / STAGES) & 1) ^ 1);
          if (elect_one()) {
            mbar_expect_tx(fb, bytes);
            tma_load_mc(sa + rank * 8192, ma, fb, ka + ko, row0 + rank * 64, (it < 20 || fl == 1) ? pol_normal : pol_stream);
            if (MODE == 1) {
              #pragma unroll
              for (int b = 0; b < 3; b++) tma_load(sa + A_BYTES + b * 8192, mb, fb, nb0 + b * 64, ko);
            }
          }
          if (MODE == 0) {
            if (fl == 1) wait_box(k + (k >= skip ? 1 : 0));
            else if (k == 0 && fl >= 0) wait_dep(fl);
            if (elect_one()) tma_load(sa + A_BYTES, mb, fb, kb + ko, nb0);
          }
        }
      };
      constexpr uint32_t B160 = A_BYTES + 160 * 128, B192 = A_BYTES + 192 * 128;
      if (elect_one()) {
        #pragma unroll
        for (int s = 0; s < STAGES; s++) {
          const uint32_t sb = c.base + s * STAGE_BYTES + A_BYTES, fb = c.bar(B_FULL + s);
          mbar_expect_tx(fb, isG ? B192 : B160);
          if (isG) {
            #pragma unroll
            for (int b = 0; b < 3; b++) tma_load(sb + b * 8192, &maps.m[M_WIN], fb, FH + ct * 192 + b * 64, s * 64);
          } else tma_load(sb, &maps.m[M_HRE], fb, s * 64, ct * 160);
        }
      }
      cluster_wait();
      wait_dep(0);
      if (elect_one()) {
        #pragma unroll
        for (int s = 0; s < STAGES; s++) tma_load_mc(c.base + s * STAGE_BYTES + rank * 8192, &maps.m[M_X], c.bar(B_FULL + s), s * 64, row0 + rank * 64, pol_normal);
      }
      it = STAGES;
      if (isG) {
        #pragma unroll 1
        for (int t = 0; t < 2; t++) run(IC<1>(), &maps.m[M_X], &maps.m[M_WIN], 0, 0, 64, 99, t ? 0 : STAGES, 10, (t ? 0 : FH) + ct * 192, B192, -1);
        run(IC<2>(), &maps.m[M_WSP], &maps.m[M_WSP], row0, 0, 64, 99, 0, 2, 0, A_BYTES, -1);
      }
      #pragma unroll 1
      for (int sg = 0; sg < (isG ? 3 : 2); sg++) {
        const CUtensorMap *ma, *mb; int ka = 0, kb = 0, ks = 64, skip = 99, n, nb0 = ct * 160, fl = -1; uint32_t bytes = B160;
        if (!isG) {
          ma = &maps.m[M_X]; mb = &maps.m[M_HRE + sg]; n = 10;
        } else if (sg < 2) {
          ma = &maps.m[M_WSP]; mb = &maps.m[M_Z2NT]; n = 15; ka = kb = sg * 64; ks = 128; skip = rb; nb0 = ct * 192; fl = 1 + sg; bytes = B192;
        } else {
          #pragma unroll 1
          for (int k = 0; k < 2; k++, it++) {
            const int s = it & (STAGES - 1);
            mbar_wait(c.bar(B_EMPTY + s), ((it / STAGES) & 1) ^ 1);
            if (elect_one()) {
              mbar_expect_tx(c.bar(B_FULL + s), 192 * 128);
              #pragma unroll
              for (int b = 0; b < 3; b++) tma_load(c.base + s * STAGE_BYTES + A_BYTES + b * 8192, &maps.m[M_XB], c.bar(B_FULL + s), ct * 160 + b * 64, row0 + k * 64);
            }
          }
          ma = &maps.m[M_SIM]; mb = &maps.m[M_ABT]; n = JSPLIT; ka = (32 - JSPLIT) * 64; kb = SEQ + ka; fl = 3;
        }
        run(IC<0>(), ma, mb, ka, kb, ks, skip, (!isG && sg == 0) ? STAGES : 0, n, nb0, bytes, fl);
      }
      if (!isG) {
        const int half = rb & 1;
        #pragma unroll 1
        for (int k = 0; k < NY + YSOLO; k++) {
          const int s = k & 3, im = k >= 16;
          const int kc = (k >= NY ? k - 16 : im ? half * (NY - 16 + YSOLO) + k - 16 : half * 16 + k) * 64;
          const uint32_t sa = c.base + s * STAGE2_BYTES, fb = c.bar(B_FULL2 + s);
          if (k < 3) { if (k == 0) mbar_wait(c.bar(B_EMPTY), 0); mbar_wait(c.bar(B_EMPTY + k + 1), 0); }
          else if (k == 3) mbar_wait(c.bar(B_SFREE2), 0);
          else mbar_wait(c.bar(B_EMPTY2 + s), ((k >> 2) & 1) ^ 1);
          if (elect_one()) {
            mbar_expect_tx(fb, k < NY ? STAGE2_BYTES : B160);
            if (k < NY) tma_load_mc(sa + rank * 16384, &maps.m[M_SRE2 + im], fb, kc, (rb >> 1) * 256 + rank * 128, pol_stream);
            else tma_load_mc(sa + half * 16384 + rank * 8192, &maps.m[M_SIM], fb, kc, row0 + rank * 64, pol_stream);
          }
          if (k < 16) { if (!(k & 1)) wait_box(half * 8 + (k >> 1)); }
          else if (k == 16) wait_dep(2);
          if (elect_one()) tma_load(sa + 32768, &maps.m[M_ABT], fb, im * SEQ + kc, ct * 160);
        }
      }
      if (isG) {
        #pragma unroll 1
        for (int k = 0; k < 12; k++, it++) {
          const int s = it & (STAGES - 1);
          const int f0 = k < 6 ? (ct ^ (k >= 3 ? 1 : 0)) * 192 + (k % 3) * 64 : ((ct >> 1) ^ 1) * 384 + (k - 6) * 64;
          const uint32_t sa = c.base + s * STAGE_BYTES, fb = c.bar(B_FULL + s);
          mbar_wait(c.bar(B_EMPTY + s), ((it / STAGES) & 1) ^ 1);
          if (elect_one()) {
            mbar_expect_tx(fb, k < 3 ? 192 * 128 : B192);
            #pragma unroll
            for (int b = 0; b < 3; b++) tma_load(sa + A_BYTES + b * 8192, &maps.m[M_WOUT], fb, ct * 160 + b * 64, f0);
          }
          if (k == 3) wait_dep(4);
          if (k == 6) wait_dep(5);
          if (k >= 3 && elect_one()) {
            if (k < 6) { tma_load(sa, &maps.m[M_HTLD], fb, row0, f0); tma_load(sa + 8192, &maps.m[M_HTLD], fb, row0 + 64, f0); }
            else tma_load_mc(sa + rank * 8192, &maps.m[M_HTLD], fb, row0 + rank * 64, f0, pol_normal);
          }
        }
        mbar_wait(c.bar(B_EMPTY + (IT_Y & 3)), ((IT_Y / STAGES) & 1) ^ 1);
        wait_dep(7);
        if (elect_one()) {
          mbar_expect_tx(c.bar(B_FULL + (IT_Y & 3)), STAGE_BYTES);
          bulk_load(c.base + (IT_Y & 3) * STAGE_BYTES, g_y + (size_t)(64 + rb * 4 + ct) * 2560, STAGE_BYTES, c.bar(B_FULL + (IT_Y & 3)));
        }
      }
    } else {
      const int ht = tid - 32;
      unsigned tk = 0;
      if (ht == 0) tk = atomicAdd(&g_ticket, 1u);
      if (c.warp == 2) {
        #pragma unroll
        for (int j = 0; j < 4; j++) {
          const int i = c.lane + j * 32;
          sts128u(c.ext(X_A) + i * 16, pack_bf16(0.5f * __bfloat162float(bsp[row0 + i]), 0.f), 0, 0, 0, 1);
          sts128u(c.ext(X_Z) + i * 16, 0, 0, 0, 0, 1);
        }
        sts128u(c.ext(X_ONES) + (ht & 7) * 16, 0x00003F80u, 0, 0, 0, ht < 40);
        #pragma unroll 1
        for (int i = c.lane; i < 512; i += 32) {
          const int r = i >> 3, ch = (i & 7) ^ (r & 7), e = ch == (r >> 3) ? (r & 7) : 8;
          const uint32_t one = (e & 1) ? 0x3F800000u : 0x00003F80u;
          sts128u(c.ext(X_ID) + i * 16, (e >> 1) == 0 ? one : 0, (e >> 1) == 1 ? one : 0, (e >> 1) == 2 ? one : 0, (e >> 1) == 3 ? one : 0, 1);
        }
        fence_async_smem();
      }
      cluster_wait();
      if (ht == 0) { sts32(c.ext(X_MASK), 0.f); sts32(c.ext(X_TAG), __uint_as_float((tk >> 7) + 1u)); mbar_arrive(c.bar(B_TAG)); }
      if (c.warp == 2) mbar_arrive(c.bar(B_TAB));
      __syncwarp();
      const unsigned tag = c.tag();
      if (c.warp == 1) {
        mbar_wait(c.bar(B_XN), 0);
        if (c.lane == 0) { flag_set(FL_XN + rb * 8 + (isG ? 4 : 0) + ct, tag); }
      }
      __syncwarp();
      if (c.warp == 3) {
        #pragma unroll 1
        for (int d = 0; d < (isG ? 8 : 3); d++) {
          const int fl = d == 0 ? FL_XN + rb * 8 + rank * 4 : !isG ? FL_AB + ((d - 1) * 4 + ct) * 16 : d < 3 ? FL_Z2N + (ct * 2 + d - 1) * 16
                         : d == 3 ? FL_AB + (4 + ct) * 16 : d == 4 ? FL_H + rb * 4 + (ct ^ 1) : d == 5 ? FL_H + rb * 4 + ((ct >> 1) ^ 1) * 2 : FL_F + (rb * 4 + ct) * 2 + d - 6;
          const int nfl = d == 0 ? 4 : d < 4 ? 16 : d == 5 ? 2 : 1;
          #pragma unroll 1
          for (int sp = 0; sp < SPIN_MAX; sp++) {
            const unsigned rdy = __ballot_sync(0xffffffffu, flag_get(fl + (c.lane & (nfl - 1))) == tag);
            if (d == 1 && c.lane == 0) asm volatile("st.release.cta.shared.u32 [%0], %1;" :: "r"(c.ext(X_MASK)), "r"(rdy) : "memory");
            if (rdy == 0xffffffffu) break;
          }
          if (c.lane == 0) mbar_arrive(c.bar(B_DEP + d));
          if (d == 6) {
            mbar_wait(c.bar(B_SFREE1), 0); mbar_wait(c.bar(B_OWN1), 0);
            fence_async_global();
            if (elect_one()) {
              mbar_expect_tx(c.bar(B_PREV), STAGE_BYTES);
              bulk_load(sbuf, g_y + (size_t)(rb * 4 + ct) * 2560, STAGE_BYTES, c.bar(B_PREV));
            }
            __syncwarp();
          }
        }
      }
      if (c.warp == 2) {
        const long long t0 = clock64();
        while (clock64() - t0 < PF_W) __nanosleep(100);
        {
          const int ln = cta * 32 + c.lane;
          #pragma unroll 1
          for (int i = ln; i < 6400; i += 4096) { prefetch_l2(hre + (size_t)i * 64); prefetch_l2(him + (size_t)i * 64); }
          #pragma unroll 1
          for (int i = ln; i < 15360; i += 4096) prefetch_l2(win + (size_t)i * 64);
          #pragma unroll 1
          for (int i = ln; i < 7680; i += 4096) prefetch_l2(wout + (size_t)i * 64);
        }
        if (isG) {
          #pragma unroll 1
          for (int i = 0; i < 10; i++) {
            while (clock64() - t0 < PF_X + i * 1000) __nanosleep(100);
            prefetch_l2(x + (size_t)(row0 + ct * 32 + c.lane) * DM + i * 64);
          }
        }
      }
      if (c.warp == 1) {
        #pragma unroll 1
        for (int job = 0; job < (isG ? 5 : 2); job++) {
          mbar_wait(c.bar(B_STORE + (job & 1)), (job >> 1) & 1);
          if (elect_one()) {
            if (isG && job >= 3) {
              #pragma unroll
              for (int b = 0; b < 5; b++) tma_store(&maps.m[M_OUT], c.base + ((IT_Y + 1) & 3) * STAGE_BYTES + b * 8192 + (job - 3) * 4096, ct * 160 + b * 32, row0 + (job - 3) * 64, 1);
              bulk_commit();
              if (job == 4) bulk_wait_read();
            } else {
              const CUtensorMap* tm = &maps.m[isG ? (job == 2 ? M_HT : M_Z2NT) : M_ABT];
              const int c0 = row0 + (isG ? 0 : job * SEQ), rows = isG ? 192 : 160;
              tma_store(tm, sbuf, c0, ct * rows, !(isG && job == 1));
              tma_store(tm, sbuf + rows * 128, c0 + 64, ct * rows, !(isG && job == 0));
              bulk_commit();
              bulk_wait_read();
              if (!(isG && job == 0)) mbar_arrive(c.bar(B_SFREE + job - (isG ? 1 : 0)));
              if (!isG && job == 1) { mbar_arrive_cluster(c.bar(B_SFREE2), 0); mbar_arrive_cluster(c.bar(B_SFREE2), 1); }
              bulk_wait_all();
              flag_set(isG ? (job == 2 ? FL_H + rb * 4 + ct : FL_Z2N + (ct * 2 + job) * 16 + rb) : FL_AB + (job * 4 + ct) * 16 + rb, tag);
            }
          }
          __syncwarp();
        }
      }
    }
  } else {
    asm volatile("setmaxnreg.inc.sync.aligned.u32 232;");
    const uint32_t a0 = stage_t_addr(c);
    {
      cp_async_wait();
      float v[40], sm = 0.f, sq = 0.f;
      #pragma unroll
      for (int i = 0; i < 5; i++) {
        const uint4 u = lds128u(xa + i * 256);
        v[8 * i] = bf_lo(u.x); v[8 * i + 1] = bf_hi(u.x); v[8 * i + 2] = bf_lo(u.y); v[8 * i + 3] = bf_hi(u.y);
        v[8 * i + 4] = bf_lo(u.z); v[8 * i + 5] = bf_hi(u.z); v[8 * i + 6] = bf_lo(u.w); v[8 * i + 7] = bf_hi(u.w);
      }
      #pragma unroll
      for (int i = 0; i < 40; i += 4) sm += (v[i] + v[i + 1]) + (v[i + 2] + v[i + 3]);
      #pragma unroll
      for (int o = 1; o < 16; o <<= 1) sm += __shfl_xor_sync(0xffffffffu, sm, o);
      const float mean = sm * (1.0f / DM);
      #pragma unroll
      for (int i = 0; i < 40; i += 2) { v[i] -= mean; v[i + 1] -= mean; sq += fmaf(v[i], v[i], v[i + 1] * v[i + 1]); }
      #pragma unroll
      for (int o = 1; o < 16; o <<= 1) sq += __shfl_xor_sync(0xffffffffu, sq, o);
      const float rstd = rsqrtf(sq * (1.0f / DM) + LN_EPS);
      uint4* dst = (uint4*)(g_xn + (size_t)(xrow + (threadIdx.x >> 4)) * DM) + (threadIdx.x & 15);
      #pragma unroll
      for (int i = 0; i < 5; i++)
        dst[i * 16] = make_uint4(pack_bf16(v[8 * i] * rstd, v[8 * i + 1] * rstd), pack_bf16(v[8 * i + 2] * rstd, v[8 * i + 3] * rstd),
                                 pack_bf16(v[8 * i + 4] * rstd, v[8 * i + 5] * rstd), pack_bf16(v[8 * i + 6] * rstd, v[8 * i + 7] * rstd));
    }
    cluster_wait();
    mbar_arrive(c.bar(B_XN));
    auto staged = [&](int job, int live) { fence_async_smem(); mbar_arrive_if(c.bar(B_STORE + (job & 1)), live); };

    const int orow = c.warp * 16 + ((c.lane >> 3) & 1) * 8 + (c.lane & 7);
    const uint32_t o0 = orow * 64 + (((c.lane >> 4) ^ ((orow >> 1) & 3)) << 4);
    float acc[2][80];
    if (!isG) {
      auto epi_ab = [&](int job, uint32_t sgn, int live) {
        #pragma unroll
        for (int mb = 0; mb < 2; mb++) {
          if (live || c.warp == mb) {
            #pragma unroll
            for (int j = 0; j < 20; j += 2)
              stmatrix_x4_t(a0 + mb * (160 * 128) + j * 1024,
                            pack_bf16(acc[mb][4 * j + 0], acc[mb][4 * j + 1]) ^ sgn, pack_bf16(acc[mb][4 * j + 2], acc[mb][4 * j + 3]) ^ sgn,
                            pack_bf16(acc[mb][4 * j + 4], acc[mb][4 * j + 5]) ^ sgn, pack_bf16(acc[mb][4 * j + 6], acc[mb][4 * j + 7]) ^ sgn, live);
          }
        }
        staged(job, live);
      };
      if (wg == 0) {
        mainloop<160, 0, 0, true>(c, acc, 0, 10, false, c.bar(B_TURN1));
        drain<160>(c, acc, 9);
      }
      epi_ab(0, 0u, wg == 0);
      if (wg == 1) {
        mbar_wait(c.bar(B_TURN1), 0);
        mainloop<160, 0, 0, true>(c, acc, 10, 10, false, 0);
        drain<160>(c, acc, 19);
        mbar_wait(c.bar(B_SFREE), 0);
      }
      epi_ab(1, 0x80008000u, wg == 1);
      wgmma_fence();
      #pragma unroll 1
      for (int k = 0; k < (wg == (rb & 1) ? NY + YSOLO : NY); k++) {
        const int s = k & 3;
        mbar_wait(c.bar(B_FULL2 + s), (k >> 2) & 1);
        const uint32_t sa = c.base + s * STAGE2_BYTES;
        const uint64_t da = make_desc(sa + wg * 16384, 16, 1024, 1), db = make_desc(sa + 32768, 16, 1024, 1);
        wgmma_fence();
        #pragma unroll
        for (int kk = 0; kk < 4; kk++)
          #pragma unroll
          for (int mb = 0; mb < 2; mb++) Wgmma<160, 0, 0>::mma(acc[mb], da + (uint64_t)(mb * 512 + kk * 2), db + (uint64_t)(kk * 2), (k | kk) ? 1 : 0);
        wgmma_commit();
        if (k > 0) { wgmma_wait<1>(); if (c.lane < (k > NY ? 4 : 2)) mbar_arrive_cluster(c.bar(B_EMPTY2 + ((k - 1) & 3)), c.lane & 1); }
      }
      wgmma_wait<0>();
      fence_acc<160>(acc);
      if (wg != (rb & 1) && c.lane < 2) mbar_arrive_cluster(c.bar(B_EMPTY2 + ((NY - 1) & 3)), c.lane);
      named_sync(1 + wg, 128);
      #pragma unroll
      for (int i = 0; i < 20; i++) {
        const float* a = &acc[i / 10][(i % 10) * 8];
        sts128u(c.base + (i >> 3) * STAGE2_BYTES + wg * 16384 + (i & 7) * 2048 + tid * 16, pack_bf16(a[0], a[1]), pack_bf16(a[2], a[3]), pack_bf16(a[4], a[5]), pack_bf16(a[6], a[7]), 1);
      }
      fence_async_smem();
      named_sync(1 + wg, 128);
      if (c.warp == 0 && elect_one()) {
        const int part = wg == (rb & 1), rbo = (rb & ~1) + wg;
        #pragma unroll
        for (int i = 0; i < 3; i++)
          bulk_store(g_y + (size_t)(part * 64 + rbo * 4 + ct) * 2560 + i * 1024, c.base + i * STAGE2_BYTES + wg * 16384, i < 2 ? 16384 : 8192);
        bulk_commit();
        const unsigned tag = c.tag();
        bulk_wait_all();
        flag_set(FL_F + (rbo * 4 + ct) * 2 + part, tag);
      }
    } else {
      float acz[2][96];
      if (wg == 0) {
        mainloop<192, 0, 1, true>(c, acz, 0, 10, false, c.bar(B_TURN1));
        drain<192>(c, acz, 9);
      }
      {
        const int live = wg == 0;
        const unsigned tag = c.tag();
        u64* const zst = &g_z2stat[(row0 + c.warp * 16 + (c.lane >> 2)) * 2];
        float s0 = 0.f, s1 = 0.f, q0 = 0.f, q1 = 0.f;
        auto gelu_part = [&](auto mb_c, auto hf_c) {
          constexpr int mb = decltype(mb_c)::value, hf = decltype(hf_c)::value;
          if (live || c.warp == mb * 2 + hf) {
            #pragma unroll
            for (int j = hf * 12; j < hf * 12 + 12; j++) {
              const float g0 = gelu2(acz[mb][4 * j]), g1 = gelu2(acz[mb][4 * j + 1]);
              const float g2 = gelu2(acz[mb][4 * j + 2]), g3 = gelu2(acz[mb][4 * j + 3]);
              acz[mb][4 * j] = g0; acz[mb][4 * j + 1] = g1; acz[mb][4 * j + 2] = g2; acz[mb][4 * j + 3] = g3;
              s0 += g0 + g1; s1 += g2 + g3;
              q0 = fmaf(g0, g0, q0); q0 = fmaf(g1, g1, q0); q1 = fmaf(g2, g2, q1); q1 = fmaf(g3, g3, q1);
            }
          }
        };
        auto publish = [&](int mb) {
          const bool up = c.lane & 2;
          float sm = (up ? s1 : s0) + __shfl_xor_sync(0xffffffffu, up ? s0 : s1, 2);
          float sq = (up ? q1 : q0) + __shfl_xor_sync(0xffffffffu, up ? q0 : q1, 2);
          sm += __shfl_xor_sync(0xffffffffu, sm, 1); sq += __shfl_xor_sync(0xffffffffu, sq, 1);
          st_tag2(zst + (mb * 64 + (up ? 8 : 0)) * 2 + ct * (SEQ * 2), tagged(sm, tag), tagged(sq, tag), live && !(c.lane & 1));
          s0 = s1 = q0 = q1 = 0.f;
        };
        uint4 e0 = make_uint4(0, 0, 0, 0), e1 = e0;
        auto fetch = [&](int mb) {
          e0 = ld_tag2(zst + mb * 128 + (c.lane & 3) * (SEQ * 2), live); e1 = ld_tag2(zst + mb * 128 + 16 + (c.lane & 3) * (SEQ * 2), live);
        };
        auto norm_stage = [&](auto mb_c) {
          constexpr int mb = decltype(mb_c)::value;
          if (live || c.warp == mb * 2) {
            #pragma unroll 1
            for (int sp = 0; sp < SPIN_MAX; sp++) {
              const bool ok = e0.y == tag && e0.w == tag && e1.y == tag && e1.w == tag;
              if (__all_sync(0xffffffffu, ok) || !live) break;
              fetch(mb);
            }
            float m0 = __uint_as_float(e0.x), v0 = __uint_as_float(e0.z), m1 = __uint_as_float(e1.x), v1 = __uint_as_float(e1.z);
            #pragma unroll
            for (int o = 1; o < 4; o <<= 1) {
              m0 += __shfl_xor_sync(0xffffffffu, m0, o); v0 += __shfl_xor_sync(0xffffffffu, v0, o);
              m1 += __shfl_xor_sync(0xffffffffu, m1, o); v1 += __shfl_xor_sync(0xffffffffu, v1, o);
            }
            m0 *= 1.0f / FH; m1 *= 1.0f / FH;
            const float r0 = 0.5f * rsqrtf(fmaxf(v0 * (1.0f / FH) - m0 * m0, 0.f) + 4.0f * LN_EPS), r1 = 0.5f * rsqrtf(fmaxf(v1 * (1.0f / FH) - m1 * m1, 0.f) + 4.0f * LN_EPS);
            const float n0 = -m0 * r0, n1 = -m1 * r1;
            #pragma unroll
            for (int j = 0; j < 24; j += 2) {
              if (mb == 0 && j == 12) fetch(1);
              stmatrix_x4_t(a0 + mb * (192 * 128) + j * 1024,
                            pack_bf16(fmaf(acz[mb][4 * j + 0], r0, n0), fmaf(acz[mb][4 * j + 1], r0, n0)), pack_bf16(fmaf(acz[mb][4 * j + 2], r1, n1), fmaf(acz[mb][4 * j + 3], r1, n1)),
                            pack_bf16(fmaf(acz[mb][4 * j + 4], r0, n0), fmaf(acz[mb][4 * j + 5], r0, n0)), pack_bf16(fmaf(acz[mb][4 * j + 6], r1, n1), fmaf(acz[mb][4 * j + 7], r1, n1)), live);
            }
            staged(mb, live);
          }
        };
        gelu_part(IC<0>(), IC<0>());
        gelu_part(IC<0>(), IC<1>());
        publish(0);
        gelu_part(IC<1>(), IC<0>());
        fetch(0);
        gelu_part(IC<1>(), IC<1>());
        publish(1);
        norm_stage(IC<0>());
        norm_stage(IC<1>());
      }
      if (wg == 1) {
        mbar_wait(c.bar(B_TURN1), 0);
        mainloop<192, 0, 1, true>(c, acz, 10, 10, false, c.bar(B_TURN0));
        drain<192>(c, acz, 19);
        mbar_wait(c.bar(B_SFREE), 0);
        mbar_wait(c.bar(B_OWN), 0);
        #pragma unroll
        for (int mb = 0; mb < 2; mb++)
          #pragma unroll
          for (int j = 0; j < 24; j += 2)
            stmatrix_x4_t(a0 + mb * (192 * 128) + j * 1024,
                          pack_bf16(acz[mb][4 * j + 0], acz[mb][4 * j + 1]), pack_bf16(acz[mb][4 * j + 2], acz[mb][4 * j + 3]),
                          pack_bf16(acz[mb][4 * j + 4], acz[mb][4 * j + 5]), pack_bf16(acz[mb][4 * j + 6], acz[mb][4 * j + 7]), 1);
      } else {
        mbar_wait(c.bar(B_STORE), 0); mbar_wait(c.bar(B_STORE1), 0);
        mbar_wait(c.bar(B_TURN0), 0);
        first_bias<192>(c, acz);
        mainloop<192, 0, 0, false, 1, 2>(c, acz, 20, 32, false, c.bar(B_TURN1));
        drain<192>(c, acz, 51);
        mbar_wait(c.bar(B_Z1RDY), 0);
      }
      if (wg == 0 || c.warp == 0) {
        const int live = wg == 0;
        uint32_t gp[24][4], z[24][4];
        #pragma unroll
        for (int i = 0; i < 24; i++)
          #pragma unroll
          for (int e = 0; e < 4; e++) gp[i][e] = pack_bf16(acz[i / 12][(i % 12) * 8 + 2 * e], acz[i / 12][(i % 12) * 8 + 2 * e + 1]);
        #pragma unroll
        for (int i = 0; i < 24; i++) ldmatrix_x4_t(a0 + i * 2048, z[i], 1);
        #pragma unroll
        for (int i = 0; i < 24; i++)
          stmatrix_x4_t(a0 + i * 2048, mul_bf16x2(z[i][0], gp[i][0]), mul_bf16x2(z[i][1], gp[i][1]), mul_bf16x2(z[i][2], gp[i][2]), mul_bf16x2(z[i][3], gp[i][3]), live);
        staged(2, live);
      }
      if (wg == 1) {
        named_sync(2, 128);
        #pragma unroll 1
        for (int i = 0; i < 24; i += 3) {
          uint4 v3[3];
          #pragma unroll
          for (int k = 0; k < 3; k++) v3[k] = lds128u(sbuf + tid * 16 + (i + k) * 2048);
          #pragma unroll
          for (int k = 0; k < 3; k++) {
            uint32_t w[4] = {v3[k].x, v3[k].y, v3[k].z, v3[k].w};
            #pragma unroll
            for (int e = 0; e < 4; e++) w[e] = pack_bf16(gelu2(bf_lo(w[e])), gelu2(bf_hi(w[e])));
            sts128u(sbuf + tid * 16 + (i + k) * 2048, w[0], w[1], w[2], w[3], 1);
          }
        }
        mbar_arrive(c.bar(B_Z1RDY));
        mbar_wait(c.bar(B_TURN1), 1);
        mbar_wait(c.bar(B_TAB), 0);
        #pragma unroll
        for (int mb = 0; mb < 2; mb++) {
          const int it = 52 + mb, s = it & (STAGES - 1);
          mbar_wait(c.bar(B_FULL + s), (it / STAGES) & 1);
          const uint64_t da = make_desc(c.ext(X_ID), 16, 1024, 1), db = make_desc(c.base + s * STAGE_BYTES + A_BYTES, 8192, 1024, 1);
          wgmma_fence();
          Wgmma<160, 0, 1>::mma_first(acc[mb], da, db);
          #pragma unroll
          for (int kk = 1; kk < 4; kk++) Wgmma<160, 0, 1>::mma(acc[mb], da + (uint64_t)(kk * 2), db + (uint64_t)(kk * 128), 1);
          wgmma_commit();
          if (mb) { wgmma_wait<1>(); release_stage(c, 52); }
        }
        mainloop<160, 0, 0, false>(c, acc, IT_F, JSPLIT, true, 0);
        mbar_wait(c.bar(B_STORE), 1);
        mainloop<160, 1, 1, false, 2, 3>(c, acc, IT_F + JSPLIT, 12, true, 0);
        drain<160>(c, acc, IT_Y - 1);
        named_sync(2, 128);
        mbar_wait(c.bar(B_PREV), 0);
        mbar_wait(c.bar(B_FULL + (IT_Y & 3)), (IT_Y / STAGES) & 1);
      }
      if (wg == 1 || c.warp == 0) {
        const int live = wg == 1;
        const uint32_t y1 = c.base + (IT_Y & 3) * STAGE_BYTES + tid * 16, ob = c.base + ((IT_Y + 1) & 3) * STAGE_BYTES + o0;
        #pragma unroll
        for (int g = 0; g < 4; g++) {
          uint4 u[5], v[5];
          #pragma unroll
          for (int i = 0; i < 5; i++) { u[i] = lds128u(sbuf + tid * 16 + (g * 5 + i) * 2048); v[i] = lds128u(y1 + (g * 5 + i) * 2048); }
          #pragma unroll
          for (int i = 0; i < 5; i++) {
            const int j = (g & 1) * 5 + i;
            const float* a = &acc[g >> 1][j * 8];
            stmatrix_x4((ob ^ ((j & 1) << 5)) + (j >> 1) * 8192 + (g >> 1) * 4096,
                        add_bf16x2(add_bf16x2(u[i].x, v[i].x), pack_bf16(a[0], a[1])), add_bf16x2(add_bf16x2(u[i].y, v[i].y), pack_bf16(a[2], a[3])),
                        add_bf16x2(add_bf16x2(u[i].z, v[i].z), pack_bf16(a[4], a[5])), add_bf16x2(add_bf16x2(u[i].w, v[i].w), pack_bf16(a[6], a[7])), live);
          }
          if (g & 1) staged(3 + (g >> 1), live);
        }
      }
    }
  }
  __syncwarp();
  cluster_arrive();
  cluster_wait();
}

typedef CUresult (*EncodeFn)(CUtensorMap*, CUtensorMapDataType, cuuint32_t, void*, const cuuint64_t*, const cuuint64_t*,
                             const cuuint32_t*, const cuuint32_t*, CUtensorMapInterleave, CUtensorMapSwizzle,
                             CUtensorMapL2promotion, CUtensorMapFloatOOBfill);

void make_map(EncodeFn enc, CUtensorMap* m, const void* p, int rows, int cols, int box_rows, int box_cols, CUtensorMapSwizzle sw) {
  cuuint64_t gd[2] = {(cuuint64_t)cols, (cuuint64_t)rows};
  cuuint64_t gs[1] = {(cuuint64_t)cols * 2};
  cuuint32_t bd[2] = {(cuuint32_t)box_cols, (cuuint32_t)box_rows};
  cuuint32_t es[2] = {1, 1};
  enc(m, CU_TENSOR_MAP_DATA_TYPE_BFLOAT16, 2, (void*)p, gd, gs, bd, es, CU_TENSOR_MAP_INTERLEAVE_NONE, sw,
      CU_TENSOR_MAP_L2_PROMOTION_L2_128B, CU_TENSOR_MAP_FLOAT_OOB_FILL_NONE);
}

}

extern "C" void kernel_launch(void* const* d_in, const int* in_sizes, int n_in, void* d_out, int out_size) {
  const __nv_bfloat16* x = (const __nv_bfloat16*)d_in[0];
  const __nv_bfloat16* sre = (const __nv_bfloat16*)d_in[1];
  const __nv_bfloat16* sim = (const __nv_bfloat16*)d_in[2];
  const __nv_bfloat16* hre = (const __nv_bfloat16*)d_in[3];
  const __nv_bfloat16* him = (const __nv_bfloat16*)d_in[4];
  const __nv_bfloat16* win = (const __nv_bfloat16*)d_in[6];
  const __nv_bfloat16* wsp = (const __nv_bfloat16*)d_in[7];
  const __nv_bfloat16* bsp = (const __nv_bfloat16*)d_in[8];
  const __nv_bfloat16* wout = (const __nv_bfloat16*)d_in[9];

  void* fn = nullptr;
  cudaDriverEntryPointQueryResult qr;
  cudaGetDriverEntryPoint("cuTensorMapEncodeTiled", &fn, cudaEnableDefault, &qr);
  EncodeFn enc = (EncodeFn)fn;
  void *p_xn, *p_abT, *p_z2nT, *p_hT;
  cudaGetSymbolAddress(&p_xn, g_xn);
  cudaGetSymbolAddress(&p_abT, g_abT);
  cudaGetSymbolAddress(&p_z2nT, g_z2nT);
  cudaGetSymbolAddress(&p_hT, g_hT);
  Maps m;
  const CUtensorMapSwizzle S128 = CU_TENSOR_MAP_SWIZZLE_128B;
  make_map(enc, &m.m[M_X], p_xn, SEQ, DM, 64, 64, S128);
  make_map(enc, &m.m[M_HRE], hre, DM, DM, 160, 64, S128);
  make_map(enc, &m.m[M_HIM], him, DM, DM, 160, 64, S128);
  make_map(enc, &m.m[M_WIN], win, DM, 2 * FH, 64, 64, S128);
  make_map(enc, &m.m[M_SRE2], sre, SEQ, SEQ, 128, 64, S128);
  make_map(enc, &m.m[M_SIM2], sim, SEQ, SEQ, 128, 64, S128);
  make_map(enc, &m.m[M_SIM], sim, SEQ, SEQ, 64, 64, S128);
  make_map(enc, &m.m[M_WSP], wsp, SEQ, SEQ, 64, 64, S128);
  make_map(enc, &m.m[M_ABT], p_abT, DM, 2 * SEQ, 160, 64, S128);
  make_map(enc, &m.m[M_Z2NT], p_z2nT, FH, SEQ, 192, 64, S128);
  make_map(enc, &m.m[M_HT], p_hT, FH, SEQ, 192, 64, S128);
  make_map(enc, &m.m[M_HTLD], p_hT, FH, SEQ, 64, 64, S128);
  make_map(enc, &m.m[M_WOUT], wout, FH, DM, 64, 64, S128);
  make_map(enc, &m.m[M_OUT], d_out, SEQ, DM, 64, 32, CU_TENSOR_MAP_SWIZZLE_64B);
  make_map(enc, &m.m[M_XB], x, SEQ, DM, 64, 64, S128);
  cudaFuncSetAttribute(fused_kernel, cudaFuncAttributeMaxDynamicSharedMemorySize, SMEM_BYTES);
  fused_kernel<<<NCTA, 384, SMEM_BYTES>>>(m, x, hre, him, win, wout, bsp);
}
```

```cpp
#include <cuda.h>
#include <cuda_runtime.h>
#include <cuda_bf16.h>
#include <stdint.h>

extern __shared__ __align__(1024) uint8_t smem_raw[];

namespace {

constexpr int SEQ = 2048, DM = 640, FH = 768;
constexpr int STAGES = 4;
constexpr int STAGE_BYTES = 40960;
constexpr int A_BYTES = 16384;
constexpr int SBUF_OFF = STAGES * STAGE_BYTES;
constexpr int EXT_OFF = SBUF_OFF + 49152;
constexpr int X_ID = 0, X_A = 8192, X_Z = 10240, X_ONES = 12288, X_TAG = 12416, X_MASK = 12420;
constexpr int BAR_OFF = EXT_OFF + 12544;
constexpr int SMEM_BYTES = BAR_OFF + 512;
constexpr int JSPLIT = 4;
constexpr int YSOLO = 4;
static_assert((JSPLIT + YSOLO) % 2 == 0, "the two F-CTAs of a tile split K evenly");
constexpr int NY = 16 + (32 - JSPLIT - YSOLO) / 2;
constexpr int IT_F = 54;
constexpr int IT_Y = IT_F + JSPLIT + 12;
constexpr int STAGE2_BYTES = 32768 + 160 * 128;
constexpr int NCTA = 128;
constexpr float LN_EPS = 1e-5f;
static_assert(SMEM_BYTES <= 232448, "smem");

enum { M_X, M_HRE, M_HIM, M_WIN, M_SRE2, M_SIM2, M_SIM, M_WSP, M_ABT, M_Z2NT, M_HT, M_HTLD, M_WOUT, M_OUT, M_XB, M_COUNT };
struct Maps { CUtensorMap m[M_COUNT]; };

typedef unsigned long long u64;
__device__ __align__(1024) __nv_bfloat16 g_xn[SEQ * DM];
__device__ __align__(1024) uint4 g_y[2 * 64 * 2560];
__device__ __align__(1024) __nv_bfloat16 g_abT[DM * 2 * SEQ];
__device__ __align__(1024) __nv_bfloat16 g_z2nT[FH * SEQ];
__device__ __align__(1024) __nv_bfloat16 g_hT[FH * SEQ];
__device__ __align__(128) u64 g_z2stat[4 * SEQ * 2];
enum { FL_AB = 0, FL_Z2N = 128, FL_H = 256, FL_F = 320, FL_XN = 448, FL_COUNT = 576 };
__device__ __align__(128) unsigned g_flags[FL_COUNT * 16];
__device__ unsigned g_ticket;

__device__ __forceinline__ void mbar_init(uint32_t bar, uint32_t cnt) { asm volatile("mbarrier.init.shared::cta.b64 [%0], %1;" :: "r"(bar), "r"(cnt) : "memory"); }
__device__ __forceinline__ void mbar_expect_tx(uint32_t bar, uint32_t bytes) { asm volatile("mbarrier.arrive.expect_tx.shared::cta.b64 _, [%0], %1;" :: "r"(bar), "r"(bytes) : "memory"); }
__device__ __forceinline__ void mbar_arrive(uint32_t bar) { asm volatile("mbarrier.arrive.shared::cta.b64 _, [%0];" :: "r"(bar) : "memory"); }
__device__ __forceinline__ void mbar_arrive_if(uint32_t bar, int live) {
  asm volatile("{\n.reg .pred p;\nsetp.ne.b32 p, %1, 0;\n@p mbarrier.arrive.shared::cta.b64 _, [%0];\n}\n" :: "r"(bar), "r"(live) : "memory");
}
__device__ __forceinline__ void mbar_arrive_cluster(uint32_t bar, uint32_t cta) {
  asm volatile("{\n.reg .b32 ra;\nmapa.shared::cluster.u32 ra, %0, %1;\nmbarrier.arrive.shared::cluster.b64 _, [ra];\n}\n" :: "r"(bar), "r"(cta) : "memory");
}
__device__ __forceinline__ void mbar_wait(uint32_t bar, uint32_t parity) {
  asm volatile("{\n.reg .pred p;\n.reg .u32 c;\nmov.u32 c, 0;\nLAB_WAIT:\n"
               "mbarrier.try_wait.parity.shared::cta.b64 p, [%0], %1;\n@p bra LAB_DONE;\n"
               "add.u32 c, c, 1;\nsetp.lt.u32 p, c, 20000;\n@p bra LAB_WAIT;\nLAB_DONE:\n}\n" :: "r"(bar), "r"(parity) : "memory");
}
__device__ __forceinline__ void tma_load(uint32_t dst, const CUtensorMap* tm, uint32_t bar, int c0, int c1) {
  asm volatile("cp.async.bulk.tensor.2d.shared::cluster.global.mbarrier::complete_tx::bytes [%0], [%1, {%3, %4}], [%2];"
    :: "r"(dst), "l"((uint64_t)tm), "r"(bar), "r"(c0), "r"(c1) : "memory");
}
__device__ __forceinline__ void tma_load_mc(uint32_t dst, const CUtensorMap* tm, uint32_t bar, int c0, int c1, uint64_t policy) {
  asm volatile("cp.async.bulk.tensor.2d.shared::cluster.global.mbarrier::complete_tx::bytes.multicast::cluster.L2::cache_hint [%0], [%1, {%3, %4}], [%2], %5, %6;"
    :: "r"(dst), "l"((uint64_t)tm), "r"(bar), "r"(c0), "r"(c1), "h"((uint16_t)3), "l"(policy) : "memory");
}
__device__ __forceinline__ void bulk_load(uint32_t dst, const void* src, uint32_t bytes, uint32_t bar) {
  asm volatile("cp.async.bulk.shared::cluster.global.mbarrier::complete_tx::bytes [%0], [%1], %2, [%3];"
    :: "r"(dst), "l"((uint64_t)src), "r"(bytes), "r"(bar) : "memory");
}
__device__ __forceinline__ void tma_store(const CUtensorMap* tm, uint32_t src, int c0, int c1) {
  asm volatile("cp.async.bulk.tensor.2d.global.shared::cta.bulk_group [%0, {%2, %3}], [%1];" :: "l"((uint64_t)tm), "r"(src), "r"(c0), "r"(c1) : "memory");
}
__device__ __forceinline__ void bulk_store(void* dst, uint32_t src, uint32_t bytes) {
  asm volatile("cp.async.bulk.global.shared::cta.bulk_group [%0], [%1], %2;" :: "l"(dst), "r"(src), "r"(bytes) : "memory");
}
__device__ __forceinline__ void bulk_commit() { asm volatile("cp.async.bulk.commit_group;" ::: "memory"); }
__device__ __forceinline__ void bulk_wait_read() { asm volatile("cp.async.bulk.wait_group.read 0;" ::: "memory"); }
__device__ __forceinline__ void bulk_wait_all() { asm volatile("cp.async.bulk.wait_group 0;" ::: "memory"); }
__device__ __forceinline__ void cp_async16(uint32_t dst, const void* src) {
  asm volatile("cp.async.cg.shared.global [%0], [%1], 16;" :: "r"(dst), "l"(src) : "memory");
}
__device__ __forceinline__ void cp_async_wait() { asm volatile("cp.async.wait_all;" ::: "memory"); }
__device__ __forceinline__ void prefetch_l2(const void* p) { asm volatile("prefetch.global.L2 [%0];" :: "l"(p)); }
__device__ __forceinline__ void prefetch_tmap(const CUtensorMap* tm) { asm volatile("prefetch.tensormap [%0];" :: "l"((uint64_t)tm) : "memory"); }
__device__ __forceinline__ void fence_async_smem() { asm volatile("fence.proxy.async.shared::cta;" ::: "memory"); }
__device__ __forceinline__ void fence_async_global() { asm volatile("fence.proxy.async.global;" ::: "memory"); }
__device__ __forceinline__ void wgmma_fence() { asm volatile("wgmma.fence.sync.aligned;" ::: "memory"); }
__device__ __forceinline__ void wgmma_commit() { asm volatile("wgmma.commit_group.sync.aligned;" ::: "memory"); }
template<int N> __device__ __forceinline__ void wgmma_wait() { asm volatile("wgmma.wait_group.sync.aligned %0;" :: "n"(N) : "memory"); }
__device__ __forceinline__ void cluster_arrive() { asm volatile("barrier.cluster.arrive.relaxed.aligned;" ::: "memory"); }
__device__ __forceinline__ void cluster_wait() { asm volatile("barrier.cluster.wait.acquire.aligned;" ::: "memory"); }
__device__ __forceinline__ bool elect_one() {
  uint32_t p; asm volatile("{\n.reg .pred p;\nelect.sync _|p, 0xffffffff;\nselp.u32 %0, 1, 0, p;\n}\n" : "=r"(p)); return p;
}
__device__ __forceinline__ void named_sync(int id, int n) { asm volatile("bar.sync %0, %1;" :: "r"(id), "r"(n) : "memory"); }
__device__ __forceinline__ void stmatrix_x4(uint32_t addr, uint32_t r0, uint32_t r1, uint32_t r2, uint32_t r3, int live) {
  asm volatile("{\n.reg .pred p;\nsetp.ne.b32 p, %5, 0;\n@p stmatrix.sync.aligned.m8n8.x4.shared.b16 [%0], {%1, %2, %3, %4};\n}\n"
    :: "r"(addr), "r"(r0), "r"(r1), "r"(r2), "r"(r3), "r"(live) : "memory");
}
__device__ __forceinline__ void stmatrix_x4_t(uint32_t addr, uint32_t r0, uint32_t r1, uint32_t r2, uint32_t r3, int live) {
  asm volatile("{\n.reg .pred p;\nsetp.ne.b32 p, %5, 0;\n@p stmatrix.sync.aligned.m8n8.x4.trans.shared.b16 [%0], {%1, %2, %3, %4};\n}\n"
    :: "r"(addr), "r"(r0), "r"(r1), "r"(r2), "r"(r3), "r"(live) : "memory");
}
__device__ __forceinline__ void ldmatrix_x4_t(uint32_t addr, uint32_t (&r)[4], int live) {
  asm volatile("{\n.reg .pred p;\nsetp.ne.b32 p, %5, 0;\n@p ldmatrix.sync.aligned.m8n8.x4.trans.shared.b16 {%0, %1, %2, %3}, [%4];\n}\n"
    : "=r"(r[0]), "=r"(r[1]), "=r"(r[2]), "=r"(r[3]) : "r"(addr), "r"(live) : "memory");
}
__device__ __forceinline__ void sts128u(uint32_t addr, uint32_t a, uint32_t b, uint32_t c, uint32_t d, int live) {
  asm volatile("{\n.reg .pred p;\nsetp.ne.b32 p, %5, 0;\n@p st.shared.v4.b32 [%0], {%1, %2, %3, %4};\n}\n" :: "r"(addr), "r"(a), "r"(b), "r"(c), "r"(d), "r"(live) : "memory");
}
__device__ __forceinline__ uint4 lds128u(uint32_t addr) {
  uint4 v; asm volatile("ld.shared.v4.u32 {%0, %1, %2, %3}, [%4];" : "=r"(v.x), "=r"(v.y), "=r"(v.z), "=r"(v.w) : "r"(addr) : "memory"); return v;
}
__device__ __forceinline__ void sts32(uint32_t addr, float a) { asm volatile("st.shared.f32 [%0], %1;" :: "r"(addr), "f"(a) : "memory"); }
__device__ __forceinline__ float lds32(uint32_t addr) { float v; asm volatile("ld.shared.f32 %0, [%1];" : "=f"(v) : "r"(addr) : "memory"); return v; }
__device__ __forceinline__ uint32_t pack_bf16(float lo, float hi) {
  uint32_t r; asm("cvt.rn.bf16x2.f32 %0, %1, %2;" : "=r"(r) : "f"(hi), "f"(lo)); return r;
}
__device__ __forceinline__ uint32_t mul_bf16x2(uint32_t a, uint32_t b) {
  uint32_t r; asm("mul.rn.bf16x2 %0, %1, %2;" : "=r"(r) : "r"(a), "r"(b)); return r;
}
__device__ __forceinline__ uint32_t add_bf16x2(uint32_t a, uint32_t b) {
  uint32_t r; asm("add.rn.bf16x2 %0, %1, %2;" : "=r"(r) : "r"(a), "r"(b)); return r;
}
__device__ __forceinline__ float bf_lo(uint32_t v) { return __uint_as_float(v << 16); }
__device__ __forceinline__ float bf_hi(uint32_t v) { return __uint_as_float(v & 0xffff0000u); }

__device__ __forceinline__ u64 tagged(float v, unsigned tag) { return ((u64)tag << 32) | __float_as_uint(v); }
__device__ __forceinline__ void st_tag2(u64* p, u64 a, u64 b, int live) {
  asm volatile("{\n.reg .pred p;\nsetp.ne.b32 p, %3, 0;\n@p st.relaxed.gpu.global.v2.b64 [%0], {%1, %2};\n}\n" :: "l"(p), "l"(a), "l"(b), "r"(live) : "memory");
}
__device__ __forceinline__ uint4 ld_tag2(const u64* p, int live) {
  u64 a = 0, b = 0;
  asm volatile("{\n.reg .pred p;\nsetp.ne.b32 p, %3, 0;\n@p ld.relaxed.gpu.global.v2.b64 {%0, %1}, [%2];\n}\n" : "+l"(a), "+l"(b) : "l"(p), "r"(live) : "memory");
  return make_uint4((uint32_t)a, (uint32_t)(a >> 32), (uint32_t)b, (uint32_t)(b >> 32));
}
__device__ __forceinline__ void flag_set(int id, unsigned tag) {
  asm volatile("fence.proxy.async.global;\nfence.acq_rel.gpu;\nst.relaxed.gpu.global.u32 [%0], %1;" :: "l"(g_flags + id * 16), "r"(tag) : "memory");
}
__device__ __forceinline__ unsigned flag_get(int id) {
  unsigned v;
  asm volatile("ld.acquire.gpu.global.u32 %0, [%1];" : "=r"(v) : "l"(g_flags + id * 16) : "memory"); return v;
}
constexpr int SPIN_MAX = 2000000;
constexpr int PF_W = 2500, PF_X = 34000;

__device__ __forceinline__ float gelu2(float v) {
  const float K1 = 0.7978845608f, K2 = 0.7978845608f * 0.044715f;
  float a = v * fmaf(v * v, K2, K1);
  float t; asm("tanh.approx.f32 %0, %1;" : "=f"(t) : "f"(a));
  return fmaf(v, t, v);
}

template<int N, int TA, int TB> struct Wgmma;
template<int TA, int TB> struct Wgmma<160, TA, TB> {
  static __device__ __forceinline__ void mma(float (&d)[80], uint64_t da, uint64_t db, int scale_d) {
    asm volatile("{\n.reg .pred p;\nsetp.ne.b32 p, %82, 0;\n"
      "wgmma.mma_async.sync.aligned.m64n160k16.f32.bf16.bf16 {%0, %1, %2, %3, %4, %5, %6, %7, %8, %9, %10, %11, %12, %13, %14, %15, %16, %17, %18, %19, %20, %21, %22, %23, %24, %25, %26, %27, %28, %29, %30, %31, %32, %33, %34, %35, %36, %37, %38, %39, %40, %41, %42, %43, %44, %45, %46, %47, %48, %49, %50, %51, %52, %53, %54, %55, %56, %57, %58, %59, %60, %61, %62, %63, %64, %65, %66, %67, %68, %69, %70, %71, %72, %73, %74, %75, %76, %77, %78, %79}, %80, %81, p, 1, 1, %83, %84;\n}\n"
      : "+f"(d[0]), "+f"(d[1]), "+f"(d[2]), "+f"(d[3]), "+f"(d[4]), "+f"(d[5]), "+f"(d[6]), "+f"(d[7]), "+f"(d[8]), "+f"(d[9]), "+f"(d[10]), "+f"(d[11]), "+f"(d[12]), "+f"(d[13]), "+f"(d[14]), "+f"(d[15]), "+f"(d[16]), "+f"(d[17]), "+f"(d[18]), "+f"(d[19]), "+f"(d[20]), "+f"(d[21]), "+f"(d[22]), "+f"(d[23]), "+f"(d[24]), "+f"(d[25]), "+f"(d[26]), "+f"(d[27]), "+f"(d[28]), "+f"(d[29]), "+f"(d[30]), "+f"(d[31]), "+f"(d[32]), "+f"(d[33]), "+f"(d[34]), "+f"(d[35]), "+f"(d[36]), "+f"(d[37]), "+f"(d[38]), "+f"(d[39]), "+f"(d[40]), "+f"(d[41]), "+f"(d[42]), "+f"(d[43]), "+f"(d[44]), "+f"(d[45]), "+f"(d[46]), "+f"(d[47]), "+f"(d[48]), "+f"(d[49]), "+f"(d[50]), "+f"(d[51]), "+f"(d[52]), "+f"(d[53]), "+f"(d[54]), "+f"(d[55]), "+f"(d[56]), "+f"(d[57]), "+f"(d[58]), "+f"(d[59]), "+f"(d[60]), "+f"(d[61]), "+f"(d[62]), "+f"(d[63]), "+f"(d[64]), "+f"(d[65]), "+f"(d[66]), "+f"(d[67]), "+f"(d[68]), "+f"(d[69]), "+f"(d[70]), "+f"(d[71]), "+f"(d[72]), "+f"(d[73]), "+f"(d[74]), "+f"(d[75]), "+f"(d[76]), "+f"(d[77]), "+f"(d[78]), "+f"(d[79])
      : "l"(da), "l"(db), "r"(scale_d), "n"(TA), "n"(TB));
  }
  static __device__ __forceinline__ void mma_first(float (&d)[80], uint64_t da, uint64_t db) {
    asm volatile("{\n.reg .pred p;\nsetp.ne.b32 p, 0, 0;\n"
      "wgmma.mma_async.sync.aligned.m64n160k16.f32.bf16.bf16 {%0, %1, %2, %3, %4, %5, %6, %7, %8, %9, %10, %11, %12, %13, %14, %15, %16, %17, %18, %19, %20, %21, %22, %23, %24, %25, %26, %27, %28, %29, %30, %31, %32, %33, %34, %35, %36, %37, %38, %39, %40, %41, %42, %43, %44, %45, %46, %47, %48, %49, %50, %51, %52, %53, %54, %55, %56, %57, %58, %59, %60, %61, %62, %63, %64, %65, %66, %67, %68, %69, %70, %71, %72, %73, %74, %75, %76, %77, %78, %79}, %80, %81, p, 1, 1, %82, %83;\n}\n"
      : "=f"(d[0]), "=f"(d[1]), "=f"(d[2]), "=f"(d[3]), "=f"(d[4]), "=f"(d[5]), "=f"(d[6]), "=f"(d[7]), "=f"(d[8]), "=f"(d[9]), "=f"(d[10]), "=f"(d[11]), "=f"(d[12]), "=f"(d[13]), "=f"(d[14]), "=f"(d[15]), "=f"(d[16]), "=f"(d[17]), "=f"(d[18]), "=f"(d[19]), "=f"(d[20]), "=f"(d[21]), "=f"(d[22]), "=f"(d[23]), "=f"(d[24]), "=f"(d[25]), "=f"(d[26]), "=f"(d[27]), "=f"(d[28]), "=f"(d[29]), "=f"(d[30]), "=f"(d[31]), "=f"(d[32]), "=f"(d[33]), "=f"(d[34]), "=f"(d[35]), "=f"(d[36]), "=f"(d[37]), "=f"(d[38]), "=f"(d[39]), "=f"(d[40]), "=f"(d[41]), "=f"(d[42]), "=f"(d[43]), "=f"(d[44]), "=f"(d[45]), "=f"(d[46]), "=f"(d[47]), "=f"(d[48]), "=f"(d[49]), "=f"(d[50]), "=f"(d[51]), "=f"(d[52]), "=f"(d[53]), "=f"(d[54]), "=f"(d[55]), "=f"(d[56]), "=f"(d[57]), "=f"(d[58]), "=f"(d[59]), "=f"(d[60]), "=f"(d[61]), "=f"(d[62]), "=f"(d[63]), "=f"(d[64]), "=f"(d[65]), "=f"(d[66]), "=f"(d[67]), "=f"(d[68]), "=f"(d[69]), "=f"(d[70]), "=f"(d[71]), "=f"(d[72]), "=f"(d[73]), "=f"(d[74]), "=f"(d[75]), "=f"(d[76]), "=f"(d[77]), "=f"(d[78]), "=f"(d[79])
      : "l"(da), "l"(db), "n"(TA), "n"(TB));
  }
};
template<int TA, int TB> struct Wgmma<192, TA, TB> {
  static __device__ __forceinline__ void mma(float (&d)[96], uint64_t da, uint64_t db, int scale_d) {
    asm volatile("{\n.reg .pred p;\nsetp.ne.b32 p, %98, 0;\n"
      "wgmma.mma_async.sync.aligned.m64n192k16.f32.bf16.bf16 {%0, %1, %2, %3, %4, %5, %6, %7, %8, %9, %10, %11, %12, %13, %14, %15, %16, %17, %18, %19, %20, %21, %22, %23, %24, %25, %26, %27, %28, %29, %30, %31, %32, %33, %34, %35, %36, %37, %38, %39, %40, %41, %42, %43, %44, %45, %46, %47, %48, %49, %50, %51, %52, %53, %54, %55, %56, %57, %58, %59, %60, %61, %62, %63, %64, %65, %66, %67, %68, %69, %70, %71, %72, %73, %74, %75, %76, %77, %78, %79, %80, %81, %82, %83, %84, %85, %86, %87, %88, %89, %90, %91, %92, %93, %94, %95}, %96, %97, p, 1, 1, %99, %100;\n}\n"
      : "+f"(d[0]), "+f"(d[1]), "+f"(d[2]), "+f"(d[3]), "+f"(d[4]), "+f"(d[5]), "+f"(d[6]), "+f"(d[7]), "+f"(d[8]), "+f"(d[9]), "+f"(d[10]), "+f"(d[11]), "+f"(d[12]), "+f"(d[13]), "+f"(d[14]), "+f"(d[15]), "+f"(d[16]), "+f"(d[17]), "+f"(d[18]), "+f"(d[19]), "+f"(d[20]), "+f"(d[21]), "+f"(d[22]), "+f"(d[23]), "+f"(d[24]), "+f"(d[25]), "+f"(d[26]), "+f"(d[27]), "+f"(d[28]), "+f"(d[29]), "+f"(d[30]), "+f"(d[31]), "+f"(d[32]), "+f"(d[33]), "+f"(d[34]), "+f"(d[35]), "+f"(d[36]), "+f"(d[37]), "+f"(d[38]), "+f"(d[39]), "+f"(d[40]), "+f"(d[41]), "+f"(d[42]), "+f"(d[43]), "+f"(d[44]), "+f"(d[45]), "+f"(d[46]), "+f"(d[47]), "+f"(d[48]), "+f"(d[49]), "+f"(d[50]), "+f"(d[51]), "+f"(d[52]), "+f"(d[53]), "+f"(d[54]), "+f"(d[55]), "+f"(d[56]), "+f"(d[57]), "+f"(d[58]), "+f"(d[59]), "+f"(d[60]), "+f"(d[61]), "+f"(d[62]), "+f"(d[63]), "+f"(d[64]), "+f"(d[65]), "+f"(d[66]), "+f"(d[67]), "+f"(d[68]), "+f"(d[69]), "+f"(d[70]), "+f"(d[71]), "+f"(d[72]), "+f"(d[73]), "+f"(d[74]), "+f"(d[75]), "+f"(d[76]), "+f"(d[77]), "+f"(d[78]), "+f"(d[79]), "+f"(d[80]), "+f"(d[81]), "+f"(d[82]), "+f"(d[83]), "+f"(d[84]), "+f"(d[85]), "+f"(d[86]), "+f"(d[87]), "+f"(d[88]), "+f"(d[89]), "+f"(d[90]), "+f"(d[91]), "+f"(d[92]), "+f"(d[93]), "+f"(d[94]), "+f"(d[95])
      : "l"(da), "l"(db), "r"(scale_d), "n"(TA), "n"(TB));
  }
  static __device__ __forceinline__ void mma_first(float (&d)[96], uint64_t da, uint64_t db) {
    asm volatile("{\n.reg .pred p;\nsetp.ne.b32 p, 0, 0;\n"
      "wgmma.mma_async.sync.aligned.m64n192k16.f32.bf16.bf16 {%0, %1, %2, %3, %4, %5, %6, %7, %8, %9, %10, %11, %12, %13, %14, %15, %16, %17, %18, %19, %20, %21, %22, %23, %24, %25, %26, %27, %28, %29, %30, %31, %32, %33, %34, %35, %36, %37, %38, %39, %40, %41, %42, %43, %44, %45, %46, %47, %48, %49, %50, %51, %52, %53, %54, %55, %56, %57, %58, %59, %60, %61, %62, %63, %64, %65, %66, %67, %68, %69, %70, %71, %72, %73, %74, %75, %76, %77, %78, %79, %80, %81, %82, %83, %84, %85, %86, %87, %88, %89, %90, %91, %92, %93, %94, %95}, %96, %97, p, 1, 1, %98, %99;\n}\n"
      : "=f"(d[0]), "=f"(d[1]), "=f"(d[2]), "=f"(d[3]), "=f"(d[4]), "=f"(d[5]), "=f"(d[6]), "=f"(d[7]), "=f"(d[8]), "=f"(d[9]), "=f"(d[10]), "=f"(d[11]), "=f"(d[12]), "=f"(d[13]), "=f"(d[14]), "=f"(d[15]), "=f"(d[16]), "=f"(d[17]), "=f"(d[18]), "=f"(d[19]), "=f"(d[20]), "=f"(d[21]), "=f"(d[22]), "=f"(d[23]), "=f"(d[24]), "=f"(d[25]), "=f"(d[26]), "=f"(d[27]), "=f"(d[28]), "=f"(d[29]), "=f"(d[30]), "=f"(d[31]), "=f"(d[32]), "=f"(d[33]), "=f"(d[34]), "=f"(d[35]), "=f"(d[36]), "=f"(d[37]), "=f"(d[38]), "=f"(d[39]), "=f"(d[40]), "=f"(d[41]), "=f"(d[42]), "=f"(d[43]), "=f"(d[44]), "=f"(d[45]), "=f"(d[46]), "=f"(d[47]), "=f"(d[48]), "=f"(d[49]), "=f"(d[50]), "=f"(d[51]), "=f"(d[52]), "=f"(d[53]), "=f"(d[54]), "=f"(d[55]), "=f"(d[56]), "=f"(d[57]), "=f"(d[58]), "=f"(d[59]), "=f"(d[60]), "=f"(d[61]), "=f"(d[62]), "=f"(d[63]), "=f"(d[64]), "=f"(d[65]), "=f"(d[66]), "=f"(d[67]), "=f"(d[68]), "=f"(d[69]), "=f"(d[70]), "=f"(d[71]), "=f"(d[72]), "=f"(d[73]), "=f"(d[74]), "=f"(d[75]), "=f"(d[76]), "=f"(d[77]), "=f"(d[78]), "=f"(d[79]), "=f"(d[80]), "=f"(d[81]), "=f"(d[82]), "=f"(d[83]), "=f"(d[84]), "=f"(d[85]), "=f"(d[86]), "=f"(d[87]), "=f"(d[88]), "=f"(d[89]), "=f"(d[90]), "=f"(d[91]), "=f"(d[92]), "=f"(d[93]), "=f"(d[94]), "=f"(d[95])
      : "l"(da), "l"(db), "n"(TA), "n"(TB));
  }
};


__device__ __forceinline__ uint64_t make_desc(uint32_t addr, uint32_t lbo, uint32_t sbo, uint32_t swz) {
  return (uint64_t)((addr & 0x3FFFF) >> 4) | ((uint64_t)(lbo >> 4) << 16) | ((uint64_t)(sbo >> 4) << 32) | ((uint64_t)swz << 62);
}

enum { B_FULL = 0, B_EMPTY = STAGES, B_SFREE = 2 * STAGES, B_SFREE1, B_Z1RDY, B_TURN0, B_TURN1, B_TAB, B_OWN, B_OWN1, B_PREV, B_TAG, B_STORE, B_XN = B_STORE + 6, B_SFREE2, B_FULL2, B_EMPTY2 = B_FULL2 + 4, B_DEP = B_EMPTY2 + 4, B_COUNT = B_DEP + 8 };

template<int V> struct IC { static constexpr int value = V; };
struct Ctx {
  uint32_t base;
  int warp, lane;
  __device__ __forceinline__ uint32_t bar(int i) const { return base + BAR_OFF + 8 * i; }
  __device__ __forceinline__ uint32_t ext(int off) const { return base + EXT_OFF + off; }
  __device__ __forceinline__ unsigned tag() const { mbar_wait(bar(B_TAG), 0); return __float_as_uint(lds32(ext(X_TAG))); }
};

__device__ __forceinline__ void release_stage(const Ctx& c, int it) {
  if (c.lane < 2) mbar_arrive_cluster(c.bar(B_EMPTY + (it & (STAGES - 1))), c.lane);
}

template<int N, int TA, int TB, bool ZI, int OWN = 0, int NOWN = 0>
__device__ __forceinline__ void mainloop(const Ctx& c, float (&acc)[2][N / 2], int it0, int n, bool pend, uint32_t pass_bar) {
  wgmma_fence();
  #pragma unroll 1
  for (int k = 0; k < n; k++) {
    int it = it0 + k, s = it & (STAGES - 1);
    mbar_wait(c.bar(B_FULL + s), (it / STAGES) & 1);
    if (pass_bar && k == n - 1 && c.lane == 0 && c.warp == 0) mbar_arrive(pass_bar);
    uint32_t sa = c.base + s * STAGE_BYTES, sb = sa + A_BYTES, mstep = 512;
    if (OWN == 1 && k < NOWN) sb = c.base + SBUF_OFF + k * (192 * 128);
    if (OWN == 2 && k < NOWN) { sa = c.base + SBUF_OFF + k * 8192; mstep = 192 * 128 / 16; }
    uint64_t da = make_desc(sa, TA == 0 ? 16 : 8192, 1024, 1);
    uint64_t db = make_desc(sb, TB == 0 ? 16 : 8192, 1024, 1);
    wgmma_fence();
    #pragma unroll
    for (int kk = 0; kk < 4; kk++) {
      int sd = (ZI && k == 0 && kk == 0) ? 0 : 1;
      #pragma unroll
      for (int mb = 0; mb < 2; mb++)
        Wgmma<N, TA, TB>::mma(acc[mb], da + (uint64_t)(mb * mstep + (TA == 0 ? kk * 2 : kk * 128)), db + (uint64_t)(TB == 0 ? kk * 2 : kk * 128), sd);
    }
    wgmma_commit();
    wgmma_wait<1>();
    if (k > 0 || pend) release_stage(c, it - 1);
    if (OWN && k == NOWN && c.lane == 0) mbar_arrive(c.bar(B_OWN + OWN - 1));
  }
}
template<int N>
__device__ __forceinline__ void fence_acc(float (&acc)[2][N / 2]) {
  #pragma unroll
  for (int mb = 0; mb < 2; mb++)
    #pragma unroll
    for (int e = 0; e < N / 2; e++) asm volatile("" : "+f"(acc[mb][e]) :: "memory");
}
template<int N>
__device__ __forceinline__ void drain(const Ctx& c, float (&acc)[2][N / 2], int it_last) {
  wgmma_wait<0>();
  fence_acc<N>(acc);
  release_stage(c, it_last);
}
template<int N>
__device__ __forceinline__ void first_bias(const Ctx& c, float (&acc)[2][N / 2]) {
  mbar_wait(c.bar(B_TAB), 0);
  uint64_t da = make_desc(c.ext(X_A), 2048, 128, 0), db = make_desc(c.ext(X_ONES), 0, 0, 0);
  wgmma_fence();
  Wgmma<N, 0, 0>::mma_first(acc[0], da, db);
  Wgmma<N, 0, 0>::mma_first(acc[1], da + 64, db);
  wgmma_commit();
}

__device__ __forceinline__ uint32_t stage_t_addr(const Ctx& c) {
  int mi = c.lane >> 3, r = c.lane & 7;
  return c.base + SBUF_OFF + ((mi >> 1) * 8 + r) * 128 + (((2 * c.warp + (mi & 1)) ^ r) << 4);
}

__global__ void __cluster_dims__(2, 1, 1) __launch_bounds__(384, 1)
fused_kernel(const __grid_constant__ Maps maps, const __nv_bfloat16* __restrict__ x, const __nv_bfloat16* __restrict__ hre,
             const __nv_bfloat16* __restrict__ him, const __nv_bfloat16* __restrict__ win, const __nv_bfloat16* __restrict__ wout,
             const __nv_bfloat16* __restrict__ bsp) {
  Ctx c;
  asm("mov.u32 %0, smem_raw;" : "=r"(c.base));
  if (threadIdx.x == 1023) smem_raw[0] = 0;
  const int wg = __shfl_sync(0xffffffffu, threadIdx.x >> 7, 0), tid = threadIdx.x & 127;
  c.warp = __shfl_sync(0xffffffffu, tid >> 5, 0); c.lane = tid & 31;
  const int cta = blockIdx.x, rank = cta & 1, pair = cta >> 1;
  const bool isG = (pair >> 3) & 1;
  const int q = (pair >> 4) * 8 + (pair & 7), rb = q >> 1, ct = (q & 1) * 2 + rank;
  const int row0 = rb * 128;
  const uint32_t sbuf = c.base + SBUF_OFF;

  const int xrow = row0 + ((isG ? 4 : 0) + ct) * 16;
  const uint32_t xa = sbuf + (threadIdx.x >> 4) * 1280 + (threadIdx.x & 15) * 16;
  if (wg < 2) {
    #pragma unroll
    for (int i = 0; i < 5; i++) cp_async16(xa + i * 256, x + (size_t)(xrow + (threadIdx.x >> 4)) * DM + (threadIdx.x & 15) * 8 + i * 128);
  }
  if (threadIdx.x == 256) {
    #pragma unroll
    for (int s = 0; s < B_COUNT; s++)
      mbar_init(c.bar(s), (s >= B_EMPTY && s < B_EMPTY + STAGES) ? 8 : (s == B_Z1RDY || (s >= B_STORE && s < B_XN)) ? 128 : s == B_TAB ? 32 : (s == B_OWN || s == B_OWN1) ? 4 : s == B_XN ? 256 : (s >= B_EMPTY2 && s < B_EMPTY2 + 4) ? 16 : s == B_SFREE2 ? 2 : 1);
    asm volatile("fence.mbarrier_init.release.cluster;" ::: "memory");
  } else if (threadIdx.x >= 288 && threadIdx.x < 288 + M_COUNT) {
    prefetch_tmap(&maps.m[threadIdx.x - 288]);
  }
  __syncwarp();
  cluster_arrive();

  if (wg == 2) {
    asm volatile("setmaxnreg.dec.sync.aligned.u32 40;");
    if (c.warp == 0) {
      int it = 0;
      uint64_t pol_stream, pol_normal;
      asm("createpolicy.fractional.L2::evict_normal.b64 %0, 1.0;" : "=l"(pol_normal));
      asm("createpolicy.fractional.L2::evict_first.b64 %0, 1.0;" : "=l"(pol_stream));
      auto wait_dep = [&](int d) {
        mbar_wait(c.bar(B_DEP + d), 0);
        fence_async_global();
      };
      auto wait_box = [&](int r) {
        #pragma unroll 1
        for (int sp = 0; sp < SPIN_MAX; sp++) {
          unsigned m; asm volatile("ld.acquire.cta.shared.u32 %0, [%1];" : "=r"(m) : "r"(c.ext(X_MASK)) : "memory");
          if ((m >> r) & 1) break;
        }
        fence_async_global();
      };
      auto run = [&](auto mode_c, const CUtensorMap* ma, const CUtensorMap* mb, int ka, int kb, int ks, int skip, int k0, int n, int nb0, uint32_t bytes, int fl) {
        constexpr int MODE = decltype(mode_c)::value;
        #pragma unroll 1
        for (int k = k0; k < n; k++, it++) {
          const int s = it & (STAGES - 1), ko = (k + (k >= skip ? 1 : 0)) * ks;
          const uint32_t sa = c.base + s * STAGE_BYTES, fb = c.bar(B_FULL + s);
          mbar_wait(c.bar(B_EMPTY + s), ((it / STAGES) & 1) ^ 1);
          if (elect_one()) {
            mbar_expect_tx(fb, bytes);
            tma_load_mc(sa + rank * 8192, ma, fb, ka + ko, row0 + rank * 64, (it < 20 || fl == 1) ? pol_normal : pol_stream);
            if (MODE == 1) {
              #pragma unroll
              for (int b = 0; b < 3; b++) tma_load(sa + A_BYTES + b * 8192, mb, fb, nb0 + b * 64, ko);
            }
          }
          if (MODE == 0) {
            if (fl == 1) wait_box(k + (k >= skip ? 1 : 0));
            else if (k == 0 && fl >= 0) wait_dep(fl);
            if (elect_one()) tma_load(sa + A_BYTES, mb, fb, kb + ko, nb0);
          }
        }
      };
      constexpr uint32_t B160 = A_BYTES + 160 * 128, B192 = A_BYTES + 192 * 128;
      if (elect_one()) {
        #pragma unroll
        for (int s = 0; s < STAGES; s++) {
          const uint32_t sb = c.base + s * STAGE_BYTES + A_BYTES, fb = c.bar(B_FULL + s);
          mbar_expect_tx(fb, isG ? B192 : B160);
          if (isG) {
            #pragma unroll
            for (int b = 0; b < 3; b++) tma_load(sb + b * 8192, &maps.m[M_WIN], fb, FH + ct * 192 + b * 64, s * 64);
          } else tma_load(sb, &maps.m[M_HRE], fb, s * 64, ct * 160);
        }
      }
      cluster_wait();
      wait_dep(0);
      if (elect_one()) {
        #pragma unroll
        for (int s = 0; s < STAGES; s++) tma_load_mc(c.base + s * STAGE_BYTES + rank * 8192, &maps.m[M_X], c.bar(B_FULL + s), s * 64, row0 + rank * 64, pol_normal);
      }
      it = STAGES;
      if (isG) {
        #pragma unroll 1
        for (int t = 0; t < 2; t++) run(IC<1>(), &maps.m[M_X], &maps.m[M_WIN], 0, 0, 64, 99, t ? 0 : STAGES, 10, (t ? 0 : FH) + ct * 192, B192, -1);
        run(IC<2>(), &maps.m[M_WSP], &maps.m[M_WSP], row0, 0, 64, 99, 0, 2, 0, A_BYTES, -1);
      }
      #pragma unroll 1
      for (int sg = 0; sg < (isG ? 3 : 2); sg++) {
        const CUtensorMap *ma, *mb; int ka = 0, kb = 0, ks = 64, skip = 99, n, nb0 = ct * 160, fl = -1; uint32_t bytes = B160;
        if (!isG) {
          ma = &maps.m[M_X]; mb = &maps.m[M_HRE + sg]; n = 10;
        } else if (sg < 2) {
          ma = &maps.m[M_WSP]; mb = &maps.m[M_Z2NT]; n = 15; ka = kb = sg * 64; ks = 128; skip = rb; nb0 = ct * 192; fl = 1 + sg; bytes = B192;
        } else {
          #pragma unroll 1
          for (int k = 0; k < 2; k++, it++) {
            const int s = it & (STAGES - 1);
            mbar_wait(c.bar(B_EMPTY + s), ((it / STAGES) & 1) ^ 1);
            if (elect_one()) {
              mbar_expect_tx(c.bar(B_FULL + s), 192 * 128);
              #pragma unroll
              for (int b = 0; b < 3; b++) tma_load(c.base + s * STAGE_BYTES + A_BYTES + b * 8192, &maps.m[M_XB], c.bar(B_FULL + s), ct * 160 + b * 64, row0 + k * 64);
            }
          }
          ma = &maps.m[M_SIM]; mb = &maps.m[M_ABT]; n = JSPLIT; ka = (32 - JSPLIT) * 64; kb = SEQ + ka; fl = 3;
        }
        run(IC<0>(), ma, mb, ka, kb, ks, skip, (!isG && sg == 0) ? STAGES : 0, n, nb0, bytes, fl);
      }
      if (!isG) {
        const int half = rb & 1;
        #pragma unroll 1
        for (int k = 0; k < NY + YSOLO; k++) {
          const int s = k & 3, im = k >= 16;
          const int kc = (k >= NY ? k - 16 : im ? half * (NY - 16 + YSOLO) + k - 16 : half * 16 + k) * 64;
          const uint32_t sa = c.base + s * STAGE2_BYTES, fb = c.bar(B_FULL2 + s);
          if (k < 3) { if (k == 0) mbar_wait(c.bar(B_EMPTY), 0); mbar_wait(c.bar(B_EMPTY + k + 1), 0); }
          else if (k == 3) mbar_wait(c.bar(B_SFREE2), 0);
          else mbar_wait(c.bar(B_EMPTY2 + s), ((k >> 2) & 1) ^ 1);
          if (elect_one()) {
            mbar_expect_tx(fb, k < NY ? STAGE2_BYTES : B160);
            if (k < NY) tma_load_mc(sa + rank * 16384, &maps.m[M_SRE2 + im], fb, kc, (rb >> 1) * 256 + rank * 128, pol_stream);
            else tma_load_mc(sa + half * 16384 + rank * 8192, &maps.m[M_SIM], fb, kc, row0 + rank * 64, pol_stream);
          }
          if (k < 16) { if (!(k & 1)) wait_box(half * 8 + (k >> 1)); }
          else if (k == 16) wait_dep(2);
          if (elect_one()) tma_load(sa + 32768, &maps.m[M_ABT], fb, im * SEQ + kc, ct * 160);
        }
      }
      if (isG) {
        #pragma unroll 1
        for (int k = 0; k < 12; k++, it++) {
          const int s = it & (STAGES - 1);
          const int f0 = k < 6 ? (ct ^ (k >= 3 ? 1 : 0)) * 192 + (k % 3) * 64 : ((ct >> 1) ^ 1) * 384 + (k - 6) * 64;
          const uint32_t sa = c.base + s * STAGE_BYTES, fb = c.bar(B_FULL + s);
          mbar_wait(c.bar(B_EMPTY + s), ((it / STAGES) & 1) ^ 1);
          if (elect_one()) {
            mbar_expect_tx(fb, k < 3 ? 192 * 128 : B192);
            #pragma unroll
            for (int b = 0; b < 3; b++) tma_load(sa + A_BYTES + b * 8192, &maps.m[M_WOUT], fb, ct * 160 + b * 64, f0);
          }
          if (k == 3) wait_dep(4);
          if (k == 6) wait_dep(5);
          if (k >= 3 && elect_one()) {
            if (k < 6) { tma_load(sa, &maps.m[M_HTLD], fb, row0, f0); tma_load(sa + 8192, &maps.m[M_HTLD], fb, row0 + 64, f0); }
            else tma_load_mc(sa + rank * 8192, &maps.m[M_HTLD], fb, row0 + rank * 64, f0, pol_normal);
          }
        }
        mbar_wait(c.bar(B_EMPTY + (IT_Y & 3)), ((IT_Y / STAGES) & 1) ^ 1);
        wait_dep(7);
        if (elect_one()) {
          mbar_expect_tx(c.bar(B_FULL + (IT_Y & 3)), STAGE_BYTES);
          bulk_load(c.base + (IT_Y & 3) * STAGE_BYTES, g_y + (size_t)(64 + rb * 4 + ct) * 2560, STAGE_BYTES, c.bar(B_FULL + (IT_Y & 3)));
        }
      }
    } else {
      const int ht = tid - 32;
      unsigned tk = 0;
      if (ht == 0) tk = atomicAdd(&g_ticket, 1u);
      if (c.warp == 2) {
        #pragma unroll
        for (int j = 0; j < 4; j++) {
          const int i = c.lane + j * 32;
          sts128u(c.ext(X_A) + i * 16, pack_bf16(0.5f * __bfloat162float(bsp[row0 + i]), 0.f), 0, 0, 0, 1);
          sts128u(c.ext(X_Z) + i * 16, 0, 0, 0, 0, 1);
        }
        sts128u(c.ext(X_ONES) + (ht & 7) * 16, 0x00003F80u, 0, 0, 0, ht < 40);
        #pragma unroll 1
        for (int i = c.lane; i < 512; i += 32) {
          const int r = i >> 3, ch = (i & 7) ^ (r & 7), e = ch == (r >> 3) ? (r & 7) : 8;
          const uint32_t one = (e & 1) ? 0x3F800000u : 0x00003F80u;
          sts128u(c.ext(X_ID) + i * 16, (e >> 1) == 0 ? one : 0, (e >> 1) == 1 ? one : 0, (e >> 1) == 2 ? one : 0, (e >> 1) == 3 ? one : 0, 1);
        }
        fence_async_smem();
      }
      cluster_wait();
      if (ht == 0) { sts32(c.ext(X_MASK), 0.f); sts32(c.ext(X_TAG), __uint_as_float((tk >> 7) + 1u)); mbar_arrive(c.bar(B_TAG)); }
      if (c.warp == 2) mbar_arrive(c.bar(B_TAB));
      __syncwarp();
      const unsigned tag = c.tag();
      if (c.warp == 1) {
        mbar_wait(c.bar(B_XN), 0);
        if (c.lane == 0) { flag_set(FL_XN + rb * 8 + (isG ? 4 : 0) + ct, tag); }
      }
      __syncwarp();
      if (c.warp == 3) {
        #pragma unroll 1
        for (int d = 0; d < (isG ? 8 : 3); d++) {
          const int fl = d == 0 ? FL_XN + rb * 8 + rank * 4 : !isG ? FL_AB + ((d - 1) * 4 + ct) * 16 : d < 3 ? FL_Z2N + (ct * 2 + d - 1) * 16
                         : d == 3 ? FL_AB + (4 + ct) * 16 : d == 4 ? FL_H + rb * 4 + (ct ^ 1) : d == 5 ? FL_H + rb * 4 + ((ct >> 1) ^ 1) * 2 : FL_F + (rb * 4 + ct) * 2 + d - 6;
          const int nfl = d == 0 ? 4 : d < 4 ? 16 : d == 5 ? 2 : 1;
          #pragma unroll 1
          for (int sp = 0; sp < SPIN_MAX; sp++) {
            const unsigned rdy = __ballot_sync(0xffffffffu, flag_get(fl + (c.lane & (nfl - 1))) == tag);
            if (d == 1 && c.lane == 0) asm volatile("st.release.cta.shared.u32 [%0], %1;" :: "r"(c.ext(X_MASK)), "r"(rdy) : "memory");
            if (rdy == 0xffffffffu) break;
          }
          if (c.lane == 0) mbar_arrive(c.bar(B_DEP + d));
          if (d == 6) {
            mbar_wait(c.bar(B_SFREE1), 0); mbar_wait(c.bar(B_OWN1), 0);
            fence_async_global();
            if (elect_one()) {
              mbar_expect_tx(c.bar(B_PREV), STAGE_BYTES);
              bulk_load(sbuf, g_y + (size_t)(rb * 4 + ct) * 2560, STAGE_BYTES, c.bar(B_PREV));
            }
            __syncwarp();
          }
        }
      }
      if (c.warp == 2) {
        const long long t0 = clock64();
        while (clock64() - t0 < PF_W) __nanosleep(100);
        {
          const int ln = cta * 32 + c.lane;
          #pragma unroll 1
          for (int i = ln; i < 6400; i += 4096) { prefetch_l2(hre + (size_t)i * 64); prefetch_l2(him + (size_t)i * 64); }
          #pragma unroll 1
          for (int i = ln; i < 15360; i += 4096) prefetch_l2(win + (size_t)i * 64);
          #pragma unroll 1
          for (int i = ln; i < 7680; i += 4096) prefetch_l2(wout + (size_t)i * 64);
        }
        if (isG) {
          #pragma unroll 1
          for (int i = 0; i < 10; i++) {
            while (clock64() - t0 < PF_X + i * 1000) __nanosleep(100);
            prefetch_l2(x + (size_t)(row0 + ct * 32 + c.lane) * DM + i * 64);
          }
        }
      }
      if (c.warp == 1) {
        #pragma unroll 1
        for (int job = 0; job < (isG ? 6 : 4); job++) {
          const int t = job >> 1, hf = job & 1;
          mbar_wait(c.bar(B_STORE + job), 0);
          if (elect_one()) {
            if (t == 2) {
              #pragma unroll
              for (int b = 0; b < 5; b++) tma_store(&maps.m[M_OUT], c.base + ((IT_Y + 1) & 3) * STAGE_BYTES + b * 8192 + hf * 4096, ct * 160 + b * 32, row0 + hf * 64);
              bulk_commit();
              if (hf) bulk_wait_read();
            } else {
              const int rows = isG ? 192 : 160;
              tma_store(&maps.m[isG ? (t ? M_HT : M_Z2NT) : M_ABT], sbuf + hf * rows * 128, row0 + (isG ? 0 : t * SEQ) + hf * 64, ct * rows);
              bulk_commit();
              if (hf) {
                bulk_wait_read();
                mbar_arrive(c.bar(B_SFREE + t));
                if (!isG && t) { mbar_arrive_cluster(c.bar(B_SFREE2), 0); mbar_arrive_cluster(c.bar(B_SFREE2), 1); }
              }
              if (hf || (isG && !t)) {
                bulk_wait_all();
                flag_set(isG ? (t ? FL_H + rb * 4 + ct : FL_Z2N + (ct * 2 + hf) * 16 + rb) : FL_AB + (t * 4 + ct) * 16 + rb, tag);
              }
            }
          }
          __syncwarp();
        }
      }
    }
  } else {
    asm volatile("setmaxnreg.inc.sync.aligned.u32 232;");
    const uint32_t a0 = stage_t_addr(c);
    {
      cp_async_wait();
      float v[40], sm = 0.f, sq = 0.f;
      #pragma unroll
      for (int i = 0; i < 5; i++) {
        const uint4 u = lds128u(xa + i * 256);
        v[8 * i] = bf_lo(u.x); v[8 * i + 1] = bf_hi(u.x); v[8 * i + 2] = bf_lo(u.y); v[8 * i + 3] = bf_hi(u.y);
        v[8 * i + 4] = bf_lo(u.z); v[8 * i + 5] = bf_hi(u.z); v[8 * i + 6] = bf_lo(u.w); v[8 * i + 7] = bf_hi(u.w);
      }
      #pragma unroll
      for (int i = 0; i < 40; i += 4) sm += (v[i] + v[i + 1]) + (v[i + 2] + v[i + 3]);
      #pragma unroll
      for (int o = 1; o < 16; o <<= 1) sm += __shfl_xor_sync(0xffffffffu, sm, o);
      const float mean = sm * (1.0f / DM);
      #pragma unroll
      for (int i = 0; i < 40; i += 2) { v[i] -= mean; v[i + 1] -= mean; sq += fmaf(v[i], v[i], v[i + 1] * v[i + 1]); }
      #pragma unroll
      for (int o = 1; o < 16; o <<= 1) sq += __shfl_xor_sync(0xffffffffu, sq, o);
      const float rstd = rsqrtf(sq * (1.0f / DM) + LN_EPS);
      uint4* dst = (uint4*)(g_xn + (size_t)(xrow + (threadIdx.x >> 4)) * DM) + (threadIdx.x & 15);
      #pragma unroll
      for (int i = 0; i < 5; i++)
        dst[i * 16] = make_uint4(pack_bf16(v[8 * i] * rstd, v[8 * i + 1] * rstd), pack_bf16(v[8 * i + 2] * rstd, v[8 * i + 3] * rstd),
                                 pack_bf16(v[8 * i + 4] * rstd, v[8 * i + 5] * rstd), pack_bf16(v[8 * i + 6] * rstd, v[8 * i + 7] * rstd));
    }
    cluster_wait();
    mbar_arrive(c.bar(B_XN));
    auto staged = [&](int job, int live) { fence_async_smem(); mbar_arrive_if(c.bar(B_STORE + job), live); };

    const int orow = c.warp * 16 + ((c.lane >> 3) & 1) * 8 + (c.lane & 7);
    const uint32_t o0 = orow * 64 + (((c.lane >> 4) ^ ((orow >> 1) & 3)) << 4);
    float acc[2][80];
    if (!isG) {
      auto epi_ab = [&](int job, uint32_t sgn, int live) {
        #pragma unroll
        for (int mb = 0; mb < 2; mb++) {
          if (live || c.warp == mb) {
            #pragma unroll
            for (int j = 0; j < 20; j += 2)
              stmatrix_x4_t(a0 + mb * (160 * 128) + j * 1024,
                            pack_bf16(acc[mb][4 * j + 0], acc[mb][4 * j + 1]) ^ sgn, pack_bf16(acc[mb][4 * j + 2], acc[mb][4 * j + 3]) ^ sgn,
                            pack_bf16(acc[mb][4 * j + 4], acc[mb][4 * j + 5]) ^ sgn, pack_bf16(acc[mb][4 * j + 6], acc[mb][4 * j + 7]) ^ sgn, live);
            staged(job * 2 + mb, live);
          }
        }
      };
      if (wg == 0) {
        mainloop<160, 0, 0, true>(c, acc, 0, 10, false, c.bar(B_TURN1));
        drain<160>(c, acc, 9);
      }
      epi_ab(0, 0u, wg == 0);
      if (wg == 1) {
        mbar_wait(c.bar(B_TURN1), 0);
        mainloop<160, 0, 0, true>(c, acc, 10, 10, false, 0);
        drain<160>(c, acc, 19);
        mbar_wait(c.bar(B_SFREE), 0);
      }
      epi_ab(1, 0x80008000u, wg == 1);
      wgmma_fence();
      #pragma unroll 1
      for (int k = 0; k < (wg == (rb & 1) ? NY + YSOLO : NY); k++) {
        const int s = k & 3;
        mbar_wait(c.bar(B_FULL2 + s), (k >> 2) & 1);
        const uint32_t sa = c.base + s * STAGE2_BYTES;
        const uint64_t da = make_desc(sa + wg * 16384, 16, 1024, 1), db = make_desc(sa + 32768, 16, 1024, 1);
        wgmma_fence();
        #pragma unroll
        for (int kk = 0; kk < 4; kk++)
          #pragma unroll
          for (int mb = 0; mb < 2; mb++) Wgmma<160, 0, 0>::mma(acc[mb], da + (uint64_t)(mb * 512 + kk * 2), db + (uint64_t)(kk * 2), (k | kk) ? 1 : 0);
        wgmma_commit();
        if (k > 0) { wgmma_wait<1>(); if (c.lane < (k > NY ? 4 : 2)) mbar_arrive_cluster(c.bar(B_EMPTY2 + ((k - 1) & 3)), c.lane & 1); }
      }
      wgmma_wait<0>();
      fence_acc<160>(acc);
      if (wg != (rb & 1) && c.lane < 2) mbar_arrive_cluster(c.bar(B_EMPTY2 + ((NY - 1) & 3)), c.lane);
      named_sync(1 + wg, 128);
      #pragma unroll
      for (int i = 0; i < 20; i++) {
        const float* a = &acc[i / 10][(i % 10) * 8];
        sts128u(c.base + (i >> 3) * STAGE2_BYTES + wg * 16384 + (i & 7) * 2048 + tid * 16, pack_bf16(a[0], a[1]), pack_bf16(a[2], a[3]), pack_bf16(a[4], a[5]), pack_bf16(a[6], a[7]), 1);
      }
      fence_async_smem();
      named_sync(1 + wg, 128);
      if (c.warp == 0 && elect_one()) {
        const int part = wg == (rb & 1), rbo = (rb & ~1) + wg;
        #pragma unroll
        for (int i = 0; i < 3; i++)
          bulk_store(g_y + (size_t)(part * 64 + rbo * 4 + ct) * 2560 + i * 1024, c.base + i * STAGE2_BYTES + wg * 16384, i < 2 ? 16384 : 8192);
        bulk_commit();
        const unsigned tag = c.tag();
        bulk_wait_all();
        flag_set(FL_F + (rbo * 4 + ct) * 2 + part, tag);
      }
    } else {
      float acz[2][96];
      if (wg == 0) {
        mainloop<192, 0, 1, true>(c, acz, 0, 10, false, c.bar(B_TURN1));
        drain<192>(c, acz, 9);
      }
      {
        const int live = wg == 0;
        const unsigned tag = c.tag();
        u64* const zst = &g_z2stat[(row0 + c.warp * 16 + (c.lane >> 2)) * 2];
        float s0 = 0.f, s1 = 0.f, q0 = 0.f, q1 = 0.f;
        auto gelu_part = [&](auto mb_c, auto hf_c) {
          constexpr int mb = decltype(mb_c)::value, hf = decltype(hf_c)::value;
          if (live || c.warp == mb * 2 + hf) {
            #pragma unroll
            for (int j = hf * 12; j < hf * 12 + 12; j++) {
              const float g0 = gelu2(acz[mb][4 * j]), g1 = gelu2(acz[mb][4 * j + 1]);
              const float g2 = gelu2(acz[mb][4 * j + 2]), g3 = gelu2(acz[mb][4 * j + 3]);
              acz[mb][4 * j] = g0; acz[mb][4 * j + 1] = g1; acz[mb][4 * j + 2] = g2; acz[mb][4 * j + 3] = g3;
              s0 += g0 + g1; s1 += g2 + g3;
              q0 = fmaf(g0, g0, q0); q0 = fmaf(g1, g1, q0); q1 = fmaf(g2, g2, q1); q1 = fmaf(g3, g3, q1);
            }
          }
        };
        auto publish = [&](int mb) {
          const bool up = c.lane & 2;
          float sm = (up ? s1 : s0) + __shfl_xor_sync(0xffffffffu, up ? s0 : s1, 2);
          float sq = (up ? q1 : q0) + __shfl_xor_sync(0xffffffffu, up ? q0 : q1, 2);
          sm += __shfl_xor_sync(0xffffffffu, sm, 1); sq += __shfl_xor_sync(0xffffffffu, sq, 1);
          st_tag2(zst + (mb * 64 + (up ? 8 : 0)) * 2 + ct * (SEQ * 2), tagged(sm, tag), tagged(sq, tag), live && !(c.lane & 1));
          s0 = s1 = q0 = q1 = 0.f;
        };
        uint4 e0 = make_uint4(0, 0, 0, 0), e1 = e0;
        auto fetch = [&](int mb) {
          e0 = ld_tag2(zst + mb * 128 + (c.lane & 3) * (SEQ * 2), live); e1 = ld_tag2(zst + mb * 128 + 16 + (c.lane & 3) * (SEQ * 2), live);
        };
        auto norm_stage = [&](auto mb_c) {
          constexpr int mb = decltype(mb_c)::value;
          if (live || c.warp == mb * 2) {
            #pragma unroll 1
            for (int sp = 0; sp < SPIN_MAX; sp++) {
              const bool ok = e0.y == tag && e0.w == tag && e1.y == tag && e1.w == tag;
              if (__all_sync(0xffffffffu, ok) || !live) break;
              fetch(mb);
            }
            float m0 = __uint_as_float(e0.x), v0 = __uint_as_float(e0.z), m1 = __uint_as_float(e1.x), v1 = __uint_as_float(e1.z);
            #pragma unroll
            for (int o = 1; o < 4; o <<= 1) {
              m0 += __shfl_xor_sync(0xffffffffu, m0, o); v0 += __shfl_xor_sync(0xffffffffu, v0, o);
              m1 += __shfl_xor_sync(0xffffffffu, m1, o); v1 += __shfl_xor_sync(0xffffffffu, v1, o);
            }
            m0 *= 1.0f / FH; m1 *= 1.0f / FH;
            const float r0 = 0.5f * rsqrtf(fmaxf(v0 * (1.0f / FH) - m0 * m0, 0.f) + 4.0f * LN_EPS), r1 = 0.5f * rsqrtf(fmaxf(v1 * (1.0f / FH) - m1 * m1, 0.f) + 4.0f * LN_EPS);
            const float n0 = -m0 * r0, n1 = -m1 * r1;
            #pragma unroll
            for (int j = 0; j < 24; j += 2) {
              if (mb == 0 && j == 12) fetch(1);
              stmatrix_x4_t(a0 + mb * (192 * 128) + j * 1024,
                            pack_bf16(fmaf(acz[mb][4 * j + 0], r0, n0), fmaf(acz[mb][4 * j + 1], r0, n0)), pack_bf16(fmaf(acz[mb][4 * j + 2], r1, n1), fmaf(acz[mb][4 * j + 3], r1, n1)),
                            pack_bf16(fmaf(acz[mb][4 * j + 4], r0, n0), fmaf(acz[mb][4 * j + 5], r0, n0)), pack_bf16(fmaf(acz[mb][4 * j + 6], r1, n1), fmaf(acz[mb][4 * j + 7], r1, n1)), live);
            }
            staged(mb, live);
          }
        };
        gelu_part(IC<0>(), IC<0>());
        gelu_part(IC<0>(), IC<1>());
        publish(0);
        gelu_part(IC<1>(), IC<0>());
        fetch(0);
        gelu_part(IC<1>(), IC<1>());
        publish(1);
        norm_stage(IC<0>());
        norm_stage(IC<1>());
      }
      if (wg == 1) {
        mbar_wait(c.bar(B_TURN1), 0);
        mainloop<192, 0, 1, true>(c, acz, 10, 10, false, c.bar(B_TURN0));
        drain<192>(c, acz, 19);
        mbar_wait(c.bar(B_SFREE), 0);
        mbar_wait(c.bar(B_OWN), 0);
        #pragma unroll
        for (int mb = 0; mb < 2; mb++)
          #pragma unroll
          for (int j = 0; j < 24; j += 2)
            stmatrix_x4_t(a0 + mb * (192 * 128) + j * 1024,
                          pack_bf16(acz[mb][4 * j + 0], acz[mb][4 * j + 1]), pack_bf16(acz[mb][4 * j + 2], acz[mb][4 * j + 3]),
                          pack_bf16(acz[mb][4 * j + 4], acz[mb][4 * j + 5]), pack_bf16(acz[mb][4 * j + 6], acz[mb][4 * j + 7]), 1);
      } else {
        mbar_wait(c.bar(B_STORE), 0); mbar_wait(c.bar(B_STORE + 1), 0);
        mbar_wait(c.bar(B_TURN0), 0);
        first_bias<192>(c, acz);
        mainloop<192, 0, 0, false, 1, 2>(c, acz, 20, 32, false, c.bar(B_TURN1));
        drain<192>(c, acz, 51);
        mbar_wait(c.bar(B_Z1RDY), 0);
      }
      if (wg == 0 || c.warp == 0) {
        const int live = wg == 0;
        uint32_t gp[24][4], z[24][4];
        #pragma unroll
        for (int i = 0; i < 24; i++)
          #pragma unroll
          for (int e = 0; e < 4; e++) gp[i][e] = pack_bf16(acz[i / 12][(i % 12) * 8 + 2 * e], acz[i / 12][(i % 12) * 8 + 2 * e + 1]);
        #pragma unroll
        for (int mb = 0; mb < 2; mb++) {
          #pragma unroll
          for (int i = mb * 12; i < mb * 12 + 12; i++) ldmatrix_x4_t(a0 + i * 2048, z[i], 1);
          #pragma unroll
          for (int i = mb * 12; i < mb * 12 + 12; i++)
            stmatrix_x4_t(a0 + i * 2048, mul_bf16x2(z[i][0], gp[i][0]), mul_bf16x2(z[i][1], gp[i][1]), mul_bf16x2(z[i][2], gp[i][2]), mul_bf16x2(z[i][3], gp[i][3]), live);
          staged(2 + mb, live);
        }
      }
      if (wg == 1) {
        named_sync(2, 128);
        #pragma unroll 1
        for (int i = 0; i < 24; i += 3) {
          uint4 v3[3];
          #pragma unroll
          for (int k = 0; k < 3; k++) v3[k] = lds128u(sbuf + tid * 16 + (i + k) * 2048);
          #pragma unroll
          for (int k = 0; k < 3; k++) {
            uint32_t w[4] = {v3[k].x, v3[k].y, v3[k].z, v3[k].w};
            #pragma unroll
            for (int e = 0; e < 4; e++) w[e] = pack_bf16(gelu2(bf_lo(w[e])), gelu2(bf_hi(w[e])));
            sts128u(sbuf + tid * 16 + (i + k) * 2048, w[0], w[1], w[2], w[3], 1);
          }
        }
        mbar_arrive(c.bar(B_Z1RDY));
        mbar_wait(c.bar(B_TURN1), 1);
        mbar_wait(c.bar(B_TAB), 0);
        #pragma unroll
        for (int mb = 0; mb < 2; mb++) {
          const int it = 52 + mb, s = it & (STAGES - 1);
          mbar_wait(c.bar(B_FULL + s), (it / STAGES) & 1);
          const uint64_t da = make_desc(c.ext(X_ID), 16, 1024, 1), db = make_desc(c.base + s * STAGE_BYTES + A_BYTES, 8192, 1024, 1);
          wgmma_fence();
          Wgmma<160, 0, 1>::mma_first(acc[mb], da, db);
          #pragma unroll
          for (int kk = 1; kk < 4; kk++) Wgmma<160, 0, 1>::mma(acc[mb], da + (uint64_t)(kk * 2), db + (uint64_t)(kk * 128), 1);
          wgmma_commit();
          if (mb) { wgmma_wait<1>(); release_stage(c, 52); }
        }
        mainloop<160, 0, 0, false>(c, acc, IT_F, JSPLIT, true, 0);
        mbar_wait(c.bar(B_STORE + 2), 0); mbar_wait(c.bar(B_STORE + 3), 0);
        mainloop<160, 1, 1, false, 2, 3>(c, acc, IT_F + JSPLIT, 12, true, 0);
        drain<160>(c, acc, IT_Y - 1);
        named_sync(2, 128);
        mbar_wait(c.bar(B_PREV), 0);
        mbar_wait(c.bar(B_FULL + (IT_Y & 3)), (IT_Y / STAGES) & 1);
      }
      if (wg == 1 || c.warp == 0) {
        const int live = wg == 1;
        const uint32_t y1 = c.base + (IT_Y & 3) * STAGE_BYTES + tid * 16, ob = c.base + ((IT_Y + 1) & 3) * STAGE_BYTES + o0;
        #pragma unroll
        for (int g = 0; g < 4; g++) {
          uint4 u[5], v[5];
          #pragma unroll
          for (int i = 0; i < 5; i++) { u[i] = lds128u(sbuf + tid * 16 + (g * 5 + i) * 2048); v[i] = lds128u(y1 + (g * 5 + i) * 2048); }
          #pragma unroll
          for (int i = 0; i < 5; i++) {
            const int j = (g & 1) * 5 + i;
            const float* a = &acc[g >> 1][j * 8];
            stmatrix_x4((ob ^ ((j & 1) << 5)) + (j >> 1) * 8192 + (g >> 1) * 4096,
                        add_bf16x2(add_bf16x2(u[i].x, v[i].x), pack_bf16(a[0], a[1])), add_bf16x2(add_bf16x2(u[i].y, v[i].y), pack_bf16(a[2], a[3])),
                        add_bf16x2(add_bf16x2(u[i].z, v[i].z), pack_bf16(a[4], a[5])), add_bf16x2(add_bf16x2(u[i].w, v[i].w), pack_bf16(a[6], a[7])), live);
          }
          if (g & 1) staged(4 + (g >> 1), live);
        }
      }
    }
  }
  __syncwarp();
  cluster_arrive();
  cluster_wait();
}

typedef CUresult (*EncodeFn)(CUtensorMap*, CUtensorMapDataType, cuuint32_t, void*, const cuuint64_t*, const cuuint64_t*,
                             const cuuint32_t*, const cuuint32_t*, CUtensorMapInterleave, CUtensorMapSwizzle,
                             CUtensorMapL2promotion, CUtensorMapFloatOOBfill);

void make_map(EncodeFn enc, CUtensorMap* m, const void* p, int rows, int cols, int box_rows, int box_cols, CUtensorMapSwizzle sw) {
  cuuint64_t gd[2] = {(cuuint64_t)cols, (cuuint64_t)rows};
  cuuint64_t gs[1] = {(cuuint64_t)cols * 2};
  cuuint32_t bd[2] = {(cuuint32_t)box_cols, (cuuint32_t)box_rows};
  cuuint32_t es[2] = {1, 1};
  enc(m, CU_TENSOR_MAP_DATA_TYPE_BFLOAT16, 2, (void*)p, gd, gs, bd, es, CU_TENSOR_MAP_INTERLEAVE_NONE, sw,
      CU_TENSOR_MAP_L2_PROMOTION_L2_128B, CU_TENSOR_MAP_FLOAT_OOB_FILL_NONE);
}

}

extern "C" void kernel_launch(void* const* d_in, const int* in_sizes, int n_in, void* d_out, int out_size) {
  const __nv_bfloat16* x = (const __nv_bfloat16*)d_in[0];
  const __nv_bfloat16* sre = (const __nv_bfloat16*)d_in[1];
  const __nv_bfloat16* sim = (const __nv_bfloat16*)d_in[2];
  const __nv_bfloat16* hre = (const __nv_bfloat16*)d_in[3];
  const __nv_bfloat16* him = (const __nv_bfloat16*)d_in[4];
  const __nv_bfloat16* win = (const __nv_bfloat16*)d_in[6];
  const __nv_bfloat16* wsp = (const __nv_bfloat16*)d_in[7];
  const __nv_bfloat16* bsp = (const __nv_bfloat16*)d_in[8];
  const __nv_bfloat16* wout = (const __nv_bfloat16*)d_in[9];

  void* fn = nullptr;
  cudaDriverEntryPointQueryResult qr;
  cudaGetDriverEntryPoint("cuTensorMapEncodeTiled", &fn, cudaEnableDefault, &qr);
  EncodeFn enc = (EncodeFn)fn;
  void *p_xn, *p_abT, *p_z2nT, *p_hT;
  cudaGetSymbolAddress(&p_xn, g_xn);
  cudaGetSymbolAddress(&p_abT, g_abT);
  cudaGetSymbolAddress(&p_z2nT, g_z2nT);
  cudaGetSymbolAddress(&p_hT, g_hT);
  Maps m;
  const CUtensorMapSwizzle S128 = CU_TENSOR_MAP_SWIZZLE_128B;
  make_map(enc, &m.m[M_X], p_xn, SEQ, DM, 64, 64, S128);
  make_map(enc, &m.m[M_HRE], hre, DM, DM, 160, 64, S128);
  make_map(enc, &m.m[M_HIM], him, DM, DM, 160, 64, S128);
  make_map(enc, &m.m[M_WIN], win, DM, 2 * FH, 64, 64, S128);
  make_map(enc, &m.m[M_SRE2], sre, SEQ, SEQ, 128, 64, S128);
  make_map(enc, &m.m[M_SIM2], sim, SEQ, SEQ, 128, 64, S128);
  make_map(enc, &m.m[M_SIM], sim, SEQ, SEQ, 64, 64, S128);
  make_map(enc, &m.m[M_WSP], wsp, SEQ, SEQ, 64, 64, S128);
  make_map(enc, &m.m[M_ABT], p_abT, DM, 2 * SEQ, 160, 64, S128);
  make_map(enc, &m.m[M_Z2NT], p_z2nT, FH, SEQ, 192, 64, S128);
  make_map(enc, &m.m[M_HT], p_hT, FH, SEQ, 192, 64, S128);
  make_map(enc, &m.m[M_HTLD], p_hT, FH, SEQ, 64, 64, S128);
  make_map(enc, &m.m[M_WOUT], wout, FH, DM, 64, 64, S128);
  make_map(enc, &m.m[M_OUT], d_out, SEQ, DM, 64, 32, CU_TENSOR_MAP_SWIZZLE_64B);
  make_map(enc, &m.m[M_XB], x, SEQ, DM, 64, 64, S128);
  cudaFuncSetAttribute(fused_kernel, cudaFuncAttributeMaxDynamicSharedMemorySize, SMEM_BYTES);
  fused_kernel<<<NCTA, 384, SMEM_BYTES>>>(m, x, hre, him, win, wout, bsp);
}
```
